```python
import torch

def _softmax(x, axis=-1):
    return torch.softmax(x, dim=axis)
def _gelu(x):
    return torch.nn.functional.gelu(x, approximate="tanh")
def _silu(x):
    return torch.nn.functional.silu(x)
def _sigmoid(x):
    return torch.sigmoid(x)
def _layernorm(x, axis=-1, eps=1e-5):
    m = x.mean(dim=axis, keepdim=True)
    v = x.var(dim=axis, keepdim=True, unbiased=False)
    return (x - m) / torch.sqrt(v + eps)
def _scatter_add(tgt, idx, src, axis=0):
    return tgt.clone().index_add_(axis, idx, src)
def _segment_sum(src, seg, n):
    out = torch.zeros((n,) + src.shape[1:], dtype=src.dtype)
    return out.index_add_(0, seg, src)
def _pad(x, pw):
    flat = tuple(v for pair in reversed(pw) for v in pair)
    return torch.nn.functional.pad(x, flat)

kernel_name = 'concat_heads__ssm_conv_s5__mha_block__prompt'

def setup_inputs():

    _w = (lambda a: (lambda t: t.to(torch.bfloat16) if t.is_floating_point() else t)(torch.as_tensor(a)))
    def _A_setup():
        B, S, D = 1, 2048, 576
        P = D
        Lambda_re = -0.5 * (lambda _x: torch.exp(torch.as_tensor(_x)))((lambda *s: torch.randn(*s, dtype=torch.bfloat16) * 0.4)(P))
        Lambda_im = (lambda *s: torch.randn(*s, dtype=torch.bfloat16) * 0.8)(P) * 1.0
        B_re = (lambda *s: torch.randn(*s, dtype=torch.bfloat16) * 0.8)(P, D) * (D ** -0.5)
        B_im = (lambda *s: torch.randn(*s, dtype=torch.bfloat16) * 0.8)(P, D) * (D ** -0.5)
        C_re = (lambda *s: torch.randn(*s, dtype=torch.bfloat16) * 0.8)(D, P) * (P ** -0.5)
        C_im = (lambda *s: torch.randn(*s, dtype=torch.bfloat16) * 0.8)(D, P) * (P ** -0.5)
        log_dt = (lambda *s: torch.randn(*s, dtype=torch.bfloat16) * 0.4)(P) * 0.3 - 2.0
        Dskip = (lambda *s: torch.randn(*s, dtype=torch.bfloat16) * 0.1)(D)
        return {
            "x": _w((lambda *s: torch.randn(*s, dtype=torch.bfloat16) * 0.05)(B, S, D)),
            "Lambda_re": _w(Lambda_re),
            "Lambda_im": _w(Lambda_im),
            "B_re": _w(B_re),
            "B_im": _w(B_im),
            "C_re": _w(C_re),
            "C_im": _w(C_im),
            "log_dt": _w(log_dt),
            "Dskip": _w(Dskip),
        }
    _A_in = _A_setup()

    def _B_setup():
        B, S, D, H = 1, 2048, 576, 32
        return {
            "x": _w((lambda *s: torch.randn(*s, dtype=torch.bfloat16) * 0.2)(B, S, D)),
            "wqkv": _w((lambda *s: torch.randn(*s, dtype=torch.bfloat16) * 0.2)(D, 3 * D)),
            "wo": _w((lambda *s: torch.randn(*s, dtype=torch.bfloat16) * 0.05)(D, D)),
        }
    _B_in = _B_setup()

    return {
        "A_x": _A_in["x"],
        "A_Lambda_re": _A_in["Lambda_re"],
        "A_Lambda_im": _A_in["Lambda_im"],
        "A_B_re": _A_in["B_re"],
        "A_B_im": _A_in["B_im"],
        "A_C_re": _A_in["C_re"],
        "A_C_im": _A_in["C_im"],
        "A_log_dt": _A_in["log_dt"],
        "A_Dskip": _A_in["Dskip"],
        "B_x": _B_in["x"],
        "B_wqkv": _B_in["wqkv"],
        "B_wo": _B_in["wo"],
    }

def reference(A_x, A_Lambda_re, A_Lambda_im, A_B_re, A_B_im, A_C_re, A_C_im, A_log_dt, A_Dskip, B_x, B_wqkv, B_wo):
    def _A_ref(x, Lambda_re, Lambda_im, B_re, B_im, C_re, C_im, log_dt, Dskip):
        Bsz, L, H = x.shape
        Lam = Lambda_re + 1j * Lambda_im
        Bmat = B_re + 1j * B_im
        Cmat = C_re + 1j * C_im
        dt = torch.exp(log_dt)
        Lam_bar = torch.exp(dt * Lam)
        B_bar = ((Lam_bar - 1.0) / Lam)[:, None] * Bmat
        Bu = torch.einsum("bld,pd->blp", x + 0j, B_bar)
        h = torch.zeros_like(Bu[:, 0, :])
        hs = []
        for t in range(L):
            h = Lam_bar[None, :] * h + Bu[:, t, :]
            hs.append(h)
        hseq = torch.stack(hs, 1)
        y = 2.0 * torch.einsum("blp,dp->bld", hseq, Cmat).real + x * Dskip[None, None, :]
        return y

    def _B_ref(x, wqkv, wo):
        B, S, D = x.shape
        H = 32
        Dh = D // H
        qkv = (lambda x, *d: x.permute(*d))((x @ wqkv).reshape(B, S, 3, H, Dh), 2, 0, 3, 1, 4)
        q, k, v = qkv[0], qkv[1], qkv[2]
        scores = torch.einsum("bhqd,bhkd->bhqk", q, k) * (Dh ** -0.5)
        p = _softmax(scores, axis=-1)
        o = torch.einsum("bhqk,bhkd->bhqd", p, v)
        return (lambda x, *d: x.permute(*d))(o, 0, 2, 1, 3).reshape(B, S, D) @ wo

    a = _A_ref(A_x, A_Lambda_re, A_Lambda_im, A_B_re, A_B_im, A_C_re, A_C_im, A_log_dt, A_Dskip)
    b = _B_ref(B_x, B_wqkv, B_wo)
    return torch.concatenate([a, b], axis=-1)
```

```cpp
#include <cuda_runtime.h>
#include <cuda.h>
#include <cuda_bf16.h>
#include <cuda_fp16.h>
#include <stdint.h>

namespace {

#define DEVI __device__ __forceinline__
typedef __nv_bfloat16 bf16;

constexpr int SEQ = 2048, DM = 576;
constexpr int HS = 256 * 640;
constexpr uint32_t PM = 0xb6b6;

__device__ __align__(1024) unsigned char g_img[2 * 32 * HS];
__device__ __align__(128) float g_knorm[32 * 128];
__device__ __align__(128) bf16 g_O[SEQ * DM];
#define HT_LD 2112
__device__ __align__(128) bf16 g_HT[2 * DM * HT_LD];
__device__ __align__(128) unsigned long long g_agg[16 * DM];
__device__ __align__(128) unsigned g_cnt[32 * 49];
constexpr int CNT_TICKET = 0, CNT_H = 1, CNT_O = 17, N_CNT = 49;
constexpr unsigned long long AGG_EMPTY = 0xFFFFFFFFFFFFFFFFull;

#define STAMP(k, cta, i)
#define CSTAMP(k, cta, i)

DEVI uint32_t s2u(const void* p) { return (uint32_t)__cvta_generic_to_shared(p); }
DEVI void mbar_init(uint32_t b, int c) { asm volatile("mbarrier.init.shared::cta.b64 [%0], %1;" ::"r"(b), "r"(c) : "memory"); }
DEVI void mbar_expect(uint32_t b, uint32_t bytes) { asm volatile("mbarrier.arrive.expect_tx.shared::cta.b64 _, [%0], %1;" ::"r"(b), "r"(bytes) : "memory"); }
DEVI void mbar_arrive(uint32_t b) { asm volatile("mbarrier.arrive.shared::cta.b64 _, [%0];" ::"r"(b) : "memory"); }
DEVI bool mbar_try(uint32_t b, uint32_t ph) {
  uint32_t r;
  asm volatile("{\n.reg .pred p;\nmbarrier.try_wait.parity.shared::cta.b64 p, [%1], %2;\nselp.u32 %0, 1, 0, p;\n}" : "=r"(r) : "r"(b), "r"(ph) : "memory");
  return r;
}
DEVI void mbar_wait(uint32_t b, uint32_t ph) {
  if (mbar_try(b, ph)) return;
#pragma unroll 1
  for (int i = 0; i < (1 << 22); i++)
    if (mbar_try(b, ph)) return;
  __trap();
}
DEVI void fence_mbar_init() { asm volatile("fence.mbarrier_init.release.cluster;" ::: "memory"); }
DEVI void fence_async_smem() { asm volatile("fence.proxy.async.shared::cta;" ::: "memory"); }
DEVI void fence_async_gmem() { asm volatile("fence.proxy.async.global;" ::: "memory"); }
DEVI void cp_async16(uint32_t dst, const void* src) { asm volatile("cp.async.cg.shared.global [%0], [%1], 16;" ::"r"(dst), "l"(src) : "memory"); }
DEVI void cp_async_arrive(uint32_t bar) { asm volatile("cp.async.mbarrier.arrive.noinc.shared::cta.b64 [%0];" ::"r"(bar) : "memory"); }
DEVI void tma_store3(const CUtensorMap* m, uint32_t src, int x, int y, int z) {
  asm volatile("cp.async.bulk.tensor.3d.global.shared::cta.bulk_group [%0, {%2, %3, %4}], [%1];" ::"l"(m), "r"(src), "r"(x), "r"(y), "r"(z) : "memory");
}
DEVI void sts32(uint32_t a, uint32_t v) { asm volatile("st.shared.u32 [%0], %1;" ::"r"(a), "r"(v) : "memory"); }
DEVI void bar_sync(int id, int n) { asm volatile("bar.sync %0, %1;" ::"r"(id), "r"(n) : "memory"); }
DEVI void pdl_wait() { asm volatile("griddepcontrol.wait;" ::: "memory"); }
DEVI void pdl_launch() { asm volatile("griddepcontrol.launch_dependents;" ::: "memory"); }
DEVI void tma2(uint32_t dst, const CUtensorMap* m, int x, int y, uint32_t bar) {
  asm volatile("cp.async.bulk.tensor.2d.shared::cluster.global.mbarrier::complete_tx::bytes [%0], [%1, {%3, %4}], [%2];"
               ::"r"(dst), "l"(m), "r"(bar), "r"(x), "r"(y) : "memory");
}
DEVI void tma4(uint32_t dst, const CUtensorMap* m, int x, int y, int z, int w, uint32_t bar) {
  asm volatile("cp.async.bulk.tensor.4d.shared::cluster.global.mbarrier::complete_tx::bytes [%0], [%1, {%3, %4, %5, %6}], [%2];"
               ::"r"(dst), "l"(m), "r"(bar), "r"(x), "r"(y), "r"(z), "r"(w) : "memory");
}
DEVI void tma5(uint32_t dst, const CUtensorMap* m, int x, int y, int z, int w, int v, uint32_t bar) {
  asm volatile("cp.async.bulk.tensor.5d.shared::cluster.global.mbarrier::complete_tx::bytes [%0], [%1, {%3, %4, %5, %6, %7}], [%2];"
               ::"r"(dst), "l"(m), "r"(bar), "r"(x), "r"(y), "r"(z), "r"(w), "r"(v) : "memory");
}
DEVI void bulk_load(uint32_t dst, const void* src, uint32_t bytes, uint32_t bar) {
  asm volatile("cp.async.bulk.shared::cluster.global.mbarrier::complete_tx::bytes [%0], [%1], %2, [%3];"
               ::"r"(dst), "l"(src), "r"(bytes), "r"(bar) : "memory");
}
DEVI void l2_prefetch(const void* src, uint32_t bytes) { asm volatile("cp.async.bulk.prefetch.L2.global [%0], %1;" ::"l"(src), "r"(bytes) : "memory"); }
DEVI void prefetch_map(const CUtensorMap* m) { asm volatile("prefetch.tensormap [%0];" ::"l"(m) : "memory"); }
DEVI void wg_fence() { asm volatile("wgmma.fence.sync.aligned;" ::: "memory"); }
DEVI void wg_commit() { asm volatile("wgmma.commit_group.sync.aligned;" ::: "memory"); }
template <int N> DEVI void wg_wait() { asm volatile("wgmma.wait_group.sync.aligned %0;" ::"n"(N) : "memory"); }
DEVI uint64_t mkdesc(uint32_t addr, uint32_t lbo, uint32_t sbo, uint32_t swz) {
  return (uint64_t)((addr & 0x3FFFF) >> 4) | ((uint64_t)(lbo >> 4) << 16) | ((uint64_t)(sbo >> 4) << 32) | ((uint64_t)swz << 62);
}
DEVI unsigned ld_acquire(const unsigned* p) { unsigned v; asm volatile("ld.acquire.gpu.global.u32 %0, [%1];" : "=r"(v) : "l"(p) : "memory"); return v; }
DEVI void red_release(unsigned* p, unsigned v) { asm volatile("red.release.gpu.global.add.u32 [%0], %1;" ::"l"(p), "r"(v) : "memory"); }
DEVI void wait_count(const unsigned* p, unsigned target) {
#pragma unroll 1
  for (int i = 0; i < (1 << 23); i++)
    if (ld_acquire(p) >= target) return;
  __trap();
}
DEVI uint32_t pack_h2(float lo, float hi) { uint32_t r; asm("cvt.rn.f16x2.f32 %0, %1, %2;" : "=r"(r) : "f"(hi), "f"(lo)); return r; }
DEVI uint32_t pack_b2(float lo, float hi) { uint32_t r; asm("cvt.rn.bf16x2.f32 %0, %1, %2;" : "=r"(r) : "f"(hi), "f"(lo)); return r; }
DEVI float bf_lo(uint32_t v) { return __uint_as_float(v << 16); }
DEVI float bf_hi(uint32_t v) { return __uint_as_float(v & 0xFFFF0000u); }
DEVI float bf_round(float v) { return __bfloat162float(__float2bfloat16_rn(v)); }

__device__ __forceinline__ void mma_n216_tb(float (&d)[108], uint64_t da, uint64_t db) {
  asm volatile("{\n.reg .pred p;\nsetp.ne.b32 p, 1, 0;\nwgmma.mma_async.sync.aligned.m64n216k16.f32.bf16.bf16 {"
      "%0, %1, %2, %3, %4, %5, %6, %7, %8, %9, %10, %11, %12, %13, %14, %15, %16, %17, %18, %19, %20, %21, %22, %23, "
      "%24, %25, %26, %27, %28, %29, %30, %31, %32, %33, %34, %35, %36, %37, %38, %39, %40, %41, %42, %43, %44, %45, %46, %47, "
      "%48, %49, %50, %51, %52, %53, %54, %55, %56, %57, %58, %59, %60, %61, %62, %63, %64, %65, %66, %67, %68, %69, %70, %71, "
      "%72, %73, %74, %75, %76, %77, %78, %79, %80, %81, %82, %83, %84, %85, %86, %87, %88, %89, %90, %91, %92, %93, %94, %95, "
      "%96, %97, %98, %99, %100, %101, %102, %103, %104, %105, %106, %107"
      "}, %108, %109, p, 1, 1, 0, 1;\n}\n"
      :
      "+f"(d[0]), "+f"(d[1]), "+f"(d[2]), "+f"(d[3]), "+f"(d[4]), "+f"(d[5]), "+f"(d[6]), "+f"(d[7]), "+f"(d[8]), "+f"(d[9]), "+f"(d[10]), "+f"(d[11]),
      "+f"(d[12]), "+f"(d[13]), "+f"(d[14]), "+f"(d[15]), "+f"(d[16]), "+f"(d[17]), "+f"(d[18]), "+f"(d[19]), "+f"(d[20]), "+f"(d[21]), "+f"(d[22]), "+f"(d[23]),
      "+f"(d[24]), "+f"(d[25]), "+f"(d[26]), "+f"(d[27]), "+f"(d[28]), "+f"(d[29]), "+f"(d[30]), "+f"(d[31]), "+f"(d[32]), "+f"(d[33]), "+f"(d[34]), "+f"(d[35]),
      "+f"(d[36]), "+f"(d[37]), "+f"(d[38]), "+f"(d[39]), "+f"(d[40]), "+f"(d[41]), "+f"(d[42]), "+f"(d[43]), "+f"(d[44]), "+f"(d[45]), "+f"(d[46]), "+f"(d[47]),
      "+f"(d[48]), "+f"(d[49]), "+f"(d[50]), "+f"(d[51]), "+f"(d[52]), "+f"(d[53]), "+f"(d[54]), "+f"(d[55]), "+f"(d[56]), "+f"(d[57]), "+f"(d[58]), "+f"(d[59]),
      "+f"(d[60]), "+f"(d[61]), "+f"(d[62]), "+f"(d[63]), "+f"(d[64]), "+f"(d[65]), "+f"(d[66]), "+f"(d[67]), "+f"(d[68]), "+f"(d[69]), "+f"(d[70]), "+f"(d[71]),
      "+f"(d[72]), "+f"(d[73]), "+f"(d[74]), "+f"(d[75]), "+f"(d[76]), "+f"(d[77]), "+f"(d[78]), "+f"(d[79]), "+f"(d[80]), "+f"(d[81]), "+f"(d[82]), "+f"(d[83]),
      "+f"(d[84]), "+f"(d[85]), "+f"(d[86]), "+f"(d[87]), "+f"(d[88]), "+f"(d[89]), "+f"(d[90]), "+f"(d[91]), "+f"(d[92]), "+f"(d[93]), "+f"(d[94]), "+f"(d[95]),
      "+f"(d[96]), "+f"(d[97]), "+f"(d[98]), "+f"(d[99]), "+f"(d[100]), "+f"(d[101]), "+f"(d[102]), "+f"(d[103]), "+f"(d[104]), "+f"(d[105]), "+f"(d[106]), "+f"(d[107])
      : "l"(da), "l"(db));
}
__device__ __forceinline__ void mma_n128(float (&d)[64], uint64_t da, uint64_t db) {
  asm volatile("{\n.reg .pred p;\nsetp.ne.b32 p, 1, 0;\nwgmma.mma_async.sync.aligned.m64n128k16.f32.bf16.bf16 {"
      "%0, %1, %2, %3, %4, %5, %6, %7, %8, %9, %10, %11, %12, %13, %14, %15, %16, %17, %18, %19, %20, %21, %22, %23, "
      "%24, %25, %26, %27, %28, %29, %30, %31, %32, %33, %34, %35, %36, %37, %38, %39, %40, %41, %42, %43, %44, %45, %46, %47, "
      "%48, %49, %50, %51, %52, %53, %54, %55, %56, %57, %58, %59, %60, %61, %62, %63"
      "}, %64, %65, p, 1, 1, 0, 0;\n}\n"
      :
      "+f"(d[0]), "+f"(d[1]), "+f"(d[2]), "+f"(d[3]), "+f"(d[4]), "+f"(d[5]), "+f"(d[6]), "+f"(d[7]), "+f"(d[8]), "+f"(d[9]), "+f"(d[10]), "+f"(d[11]),
      "+f"(d[12]), "+f"(d[13]), "+f"(d[14]), "+f"(d[15]), "+f"(d[16]), "+f"(d[17]), "+f"(d[18]), "+f"(d[19]), "+f"(d[20]), "+f"(d[21]), "+f"(d[22]), "+f"(d[23]),
      "+f"(d[24]), "+f"(d[25]), "+f"(d[26]), "+f"(d[27]), "+f"(d[28]), "+f"(d[29]), "+f"(d[30]), "+f"(d[31]), "+f"(d[32]), "+f"(d[33]), "+f"(d[34]), "+f"(d[35]),
      "+f"(d[36]), "+f"(d[37]), "+f"(d[38]), "+f"(d[39]), "+f"(d[40]), "+f"(d[41]), "+f"(d[42]), "+f"(d[43]), "+f"(d[44]), "+f"(d[45]), "+f"(d[46]), "+f"(d[47]),
      "+f"(d[48]), "+f"(d[49]), "+f"(d[50]), "+f"(d[51]), "+f"(d[52]), "+f"(d[53]), "+f"(d[54]), "+f"(d[55]), "+f"(d[56]), "+f"(d[57]), "+f"(d[58]), "+f"(d[59]),
      "+f"(d[60]), "+f"(d[61]), "+f"(d[62]), "+f"(d[63])
      : "l"(da), "l"(db));
}
__device__ __forceinline__ void mma_n144_ta(float (&d)[72], uint64_t da, uint64_t db) {
  asm volatile("{\n.reg .pred p;\nsetp.ne.b32 p, 1, 0;\nwgmma.mma_async.sync.aligned.m64n144k16.f32.bf16.bf16 {"
      "%0, %1, %2, %3, %4, %5, %6, %7, %8, %9, %10, %11, %12, %13, %14, %15, %16, %17, %18, %19, %20, %21, %22, %23, "
      "%24, %25, %26, %27, %28, %29, %30, %31, %32, %33, %34, %35, %36, %37, %38, %39, %40, %41, %42, %43, %44, %45, %46, %47, "
      "%48, %49, %50, %51, %52, %53, %54, %55, %56, %57, %58, %59, %60, %61, %62, %63, %64, %65, %66, %67, %68, %69, %70, %71"
      "}, %72, %73, p, 1, 1, 1, 0;\n}\n"
      :
      "+f"(d[0]), "+f"(d[1]), "+f"(d[2]), "+f"(d[3]), "+f"(d[4]), "+f"(d[5]), "+f"(d[6]), "+f"(d[7]), "+f"(d[8]), "+f"(d[9]), "+f"(d[10]), "+f"(d[11]),
      "+f"(d[12]), "+f"(d[13]), "+f"(d[14]), "+f"(d[15]), "+f"(d[16]), "+f"(d[17]), "+f"(d[18]), "+f"(d[19]), "+f"(d[20]), "+f"(d[21]), "+f"(d[22]), "+f"(d[23]),
      "+f"(d[24]), "+f"(d[25]), "+f"(d[26]), "+f"(d[27]), "+f"(d[28]), "+f"(d[29]), "+f"(d[30]), "+f"(d[31]), "+f"(d[32]), "+f"(d[33]), "+f"(d[34]), "+f"(d[35]),
      "+f"(d[36]), "+f"(d[37]), "+f"(d[38]), "+f"(d[39]), "+f"(d[40]), "+f"(d[41]), "+f"(d[42]), "+f"(d[43]), "+f"(d[44]), "+f"(d[45]), "+f"(d[46]), "+f"(d[47]),
      "+f"(d[48]), "+f"(d[49]), "+f"(d[50]), "+f"(d[51]), "+f"(d[52]), "+f"(d[53]), "+f"(d[54]), "+f"(d[55]), "+f"(d[56]), "+f"(d[57]), "+f"(d[58]), "+f"(d[59]),
      "+f"(d[60]), "+f"(d[61]), "+f"(d[62]), "+f"(d[63]), "+f"(d[64]), "+f"(d[65]), "+f"(d[66]), "+f"(d[67]), "+f"(d[68]), "+f"(d[69]), "+f"(d[70]), "+f"(d[71])
      : "l"(da), "l"(db));
}
__device__ __forceinline__ void mma_n80_ta(float (&d)[40], uint64_t da, uint64_t db) {
  asm volatile("{\n.reg .pred p;\nsetp.ne.b32 p, 1, 0;\nwgmma.mma_async.sync.aligned.m64n80k16.f32.bf16.bf16 {"
      "%0, %1, %2, %3, %4, %5, %6, %7, %8, %9, %10, %11, %12, %13, %14, %15, %16, %17, %18, %19, %20, %21, %22, %23, "
      "%24, %25, %26, %27, %28, %29, %30, %31, %32, %33, %34, %35, %36, %37, %38, %39"
      "}, %40, %41, p, 1, 1, 1, 0;\n}\n"
      :
      "+f"(d[0]), "+f"(d[1]), "+f"(d[2]), "+f"(d[3]), "+f"(d[4]), "+f"(d[5]), "+f"(d[6]), "+f"(d[7]), "+f"(d[8]), "+f"(d[9]), "+f"(d[10]), "+f"(d[11]),
      "+f"(d[12]), "+f"(d[13]), "+f"(d[14]), "+f"(d[15]), "+f"(d[16]), "+f"(d[17]), "+f"(d[18]), "+f"(d[19]), "+f"(d[20]), "+f"(d[21]), "+f"(d[22]), "+f"(d[23]),
      "+f"(d[24]), "+f"(d[25]), "+f"(d[26]), "+f"(d[27]), "+f"(d[28]), "+f"(d[29]), "+f"(d[30]), "+f"(d[31]), "+f"(d[32]), "+f"(d[33]), "+f"(d[34]), "+f"(d[35]),
      "+f"(d[36]), "+f"(d[37]), "+f"(d[38]), "+f"(d[39])
      : "l"(da), "l"(db));
}
__device__ __forceinline__ void qk_n128_z(uint32_t (&d)[32], uint32_t a0, uint32_t a1, uint32_t a2, uint32_t a3, uint64_t db) {
  asm volatile("{\n.reg .pred p;\nsetp.ne.b32 p, 0, 0;\nwgmma.mma_async.sync.aligned.m64n128k16.f16.f16.f16 {"
      "%0, %1, %2, %3, %4, %5, %6, %7, %8, %9, %10, %11, %12, %13, %14, %15, %16, %17, %18, %19, %20, %21, %22, %23, "
      "%24, %25, %26, %27, %28, %29, %30, %31"
      "}, {%32, %33, %34, %35}, %36, p, 1, 1, 0;\n}\n"
      :
      "=r"(d[0]), "=r"(d[1]), "=r"(d[2]), "=r"(d[3]), "=r"(d[4]), "=r"(d[5]), "=r"(d[6]), "=r"(d[7]), "=r"(d[8]), "=r"(d[9]), "=r"(d[10]), "=r"(d[11]),
      "=r"(d[12]), "=r"(d[13]), "=r"(d[14]), "=r"(d[15]), "=r"(d[16]), "=r"(d[17]), "=r"(d[18]), "=r"(d[19]), "=r"(d[20]), "=r"(d[21]), "=r"(d[22]), "=r"(d[23]),
      "=r"(d[24]), "=r"(d[25]), "=r"(d[26]), "=r"(d[27]), "=r"(d[28]), "=r"(d[29]), "=r"(d[30]), "=r"(d[31])
      : "r"(a0), "r"(a1), "r"(a2), "r"(a3), "l"(db));
}
__device__ __forceinline__ void qk_n128(uint32_t (&d)[32], uint32_t a0, uint32_t a1, uint32_t a2, uint32_t a3, uint64_t db) {
  asm volatile("{\n.reg .pred p;\nsetp.ne.b32 p, 1, 0;\nwgmma.mma_async.sync.aligned.m64n128k16.f16.f16.f16 {"
      "%0, %1, %2, %3, %4, %5, %6, %7, %8, %9, %10, %11, %12, %13, %14, %15, %16, %17, %18, %19, %20, %21, %22, %23, "
      "%24, %25, %26, %27, %28, %29, %30, %31"
      "}, {%32, %33, %34, %35}, %36, p, 1, 1, 0;\n}\n"
      :
      "+r"(d[0]), "+r"(d[1]), "+r"(d[2]), "+r"(d[3]), "+r"(d[4]), "+r"(d[5]), "+r"(d[6]), "+r"(d[7]), "+r"(d[8]), "+r"(d[9]), "+r"(d[10]), "+r"(d[11]),
      "+r"(d[12]), "+r"(d[13]), "+r"(d[14]), "+r"(d[15]), "+r"(d[16]), "+r"(d[17]), "+r"(d[18]), "+r"(d[19]), "+r"(d[20]), "+r"(d[21]), "+r"(d[22]), "+r"(d[23]),
      "+r"(d[24]), "+r"(d[25]), "+r"(d[26]), "+r"(d[27]), "+r"(d[28]), "+r"(d[29]), "+r"(d[30]), "+r"(d[31])
      : "r"(a0), "r"(a1), "r"(a2), "r"(a3), "l"(db));
}
__device__ __forceinline__ void pv_n24(float (&d)[12], uint32_t a0, uint32_t a1, uint32_t a2, uint32_t a3, uint64_t db) {
  asm volatile("{\n.reg .pred p;\nsetp.ne.b32 p, 1, 0;\nwgmma.mma_async.sync.aligned.m64n24k16.f32.f16.f16 {"
      "%0, %1, %2, %3, %4, %5, %6, %7, %8, %9, %10, %11"
      "}, {%12, %13, %14, %15}, %16, p, 1, 1, 1;\n}\n"
      :
      "+f"(d[0]), "+f"(d[1]), "+f"(d[2]), "+f"(d[3]), "+f"(d[4]), "+f"(d[5]), "+f"(d[6]), "+f"(d[7]), "+f"(d[8]), "+f"(d[9]), "+f"(d[10]), "+f"(d[11])
      : "r"(a0), "r"(a1), "r"(a2), "r"(a3), "l"(db));
}

constexpr int QST = 4, Q_A = 16384, Q_B = 32768, Q_STAGE = Q_A + Q_B, Q_SMEM = QST * Q_STAGE + 128;

struct PrefetchList { const unsigned char* p[6]; };

__global__ void __launch_bounds__(256, 1)
qkv_kernel(const __grid_constant__ CUtensorMap tmX, const __grid_constant__ CUtensorMap tmImg, const bf16* __restrict__ W, const PrefetchList pf) {
  extern __shared__ __align__(1024) unsigned char smem[];
  const int tid = threadIdx.x, warp = tid >> 5, lane = tid & 31;
  const int rb = blockIdx.x >> 3, j = blockIdx.x & 7;
  const uint32_t sb = s2u(smem), bars = sb + QST * Q_STAGE;
  if (tid == 0) {
    STAMP(0, blockIdx.x, 0);
#pragma unroll
    for (int s = 0; s < QST; s++) { mbar_init(bars + 8 * s, 257); mbar_init(bars + 8 * (QST + s), 8); }
    fence_mbar_init();
#pragma unroll
    for (int s = 0; s < QST; s++) { mbar_expect(bars + 8 * s, Q_A); tma2(sb + s * Q_STAGE, &tmX, s * 64, rb * 128, bars + 8 * s); }
  }
  uint32_t so[7], go[7];
#pragma unroll
  for (int i = 0; i < 7; i++) {
    const int p = i * 256 + tid, k = p / 27, q = p - k * 27;
    so[i] = sb + Q_A + (q >> 3) * 8192 + k * 128 + (((q & 7) ^ (k & 7)) << 4);
    go[i] = k * 3456 + q * 16;
  }
  const unsigned char* wb = (const unsigned char*)W + j * 432;
  auto load_w = [&](int kb, int s) {
#pragma unroll
    for (int i = 0; i < 7; i++)
      if (i < 6 || tid < 192) cp_async16(so[i] + s * Q_STAGE, wb + kb * (64 * 3456) + go[i]);
  };
  load_w(0, 0);
  __syncthreads();
  cp_async_arrive(bars);
#pragma unroll
  for (int s = 1; s < QST; s++) { load_w(s, s); cp_async_arrive(bars + 8 * s); }
  pdl_launch();
  if (tid >= 128 && tid < 128 + 72) g_agg[blockIdx.x * 72 + tid - 128] = AGG_EMPTY;
  if (blockIdx.x == 0 && tid >= 200 && tid < 200 + N_CNT) g_cnt[(tid - 200) * 32] = 0;

  float acc[108];
#pragma unroll
  for (int i = 0; i < 108; i++) acc[i] = 0.f;
  const uint64_t dA = mkdesc(sb + (warp >> 2) * 8192, 16, 1024, 1), dB = mkdesc(sb + Q_A, 8192, 1024, 1);
#pragma unroll
  for (int kb = 0; kb < 9; kb++) {
    const int s = kb % QST;
    mbar_wait(bars + 8 * s, (kb / QST) & 1);
    fence_async_smem();
    if (kb == 0 && tid == 0) STAMP(0, blockIdx.x, 1);
    wg_fence();
#pragma unroll
    for (int ks = 0; ks < 4; ks++) mma_n216_tb(acc, dA + (s * Q_STAGE >> 4) + ks * 2, dB + (s * Q_STAGE >> 4) + ks * 128);
    wg_commit();
    if (kb > 0) {
      wg_wait<1>();
      if (kb - 1 + QST < 9) {
        const int r = (kb - 1) % QST;
        if (lane == 0) mbar_arrive(bars + 8 * (QST + r));
        mbar_wait(bars + 8 * (QST + r), ((kb - 1) / QST) & 1);
        load_w(kb - 1 + QST, r);
        cp_async_arrive(bars + 8 * r);
        if (tid == 0) { mbar_expect(bars + 8 * r, Q_A); tma2(sb + r * Q_STAGE, &tmX, (kb - 1 + QST) * 64, rb * 128, bars + 8 * r); }
        __syncwarp();
      }
    }
    if (kb == 6) {
      if (tid == 160) {
        l2_prefetch(pf.p[0] + blockIdx.x * 18432, 18432);
#pragma unroll
        for (int i = 1; i < 6; i++) l2_prefetch(pf.p[i] + blockIdx.x * 5184, 5184);
      }
      __syncwarp();
    }
  }
  wg_wait<0>();
  __syncthreads();
  if (tid == 0) STAMP(0, blockIdx.x, 2);

  const int g = lane >> 2, c = lane & 3, wg = warp >> 2;
  uint32_t off[9];
#pragma unroll
  for (int b = 0; b < 9; b++) {
    const int col = 8 * b + 2 * c, hh = col / 18, dim = col - 18 * hh;
    off[b] = sb + wg * 24576 + hh * 2048 + (warp & 3) * 512 + g * 16 + (dim >> 3) * 128 + (dim & 7) * 2;
  }
  const bool poly0 = (PM >> (2 * warp)) & 1, poly1 = (PM >> (2 * warp + 1)) & 1;
#pragma unroll
  for (int a = 0; a < 3; a++) {
    const int ga = 3 * j + a, type = ga >> 3;
    const int slot = 4 * ga - (type == 2 ? 32 : 0);
    const float qs = 0.34004565f;
    const float s0 = type == 0 ? qs : (type == 1 && poly0 ? 0.001953125f : 1.f);
    const float s1 = type == 0 ? qs : (type == 1 && poly1 ? 0.001953125f : 1.f);
    uint32_t t0 = 0, t1 = 0;
#pragma unroll
    for (int b = 0; b < 9; b++) {
      const int i = 4 * (9 * a + b);
      const uint32_t v0 = pack_h2(acc[i] * s0, acc[i + 1] * s0), v1 = pack_h2(acc[i + 2] * s1, acc[i + 3] * s1);
      if (b >= 2 && !(b & 1) && c == (b - 2) / 2) { t0 = v0; t1 = v1; }
      else { sts32(off[b] + a * 8192, v0); sts32(off[b] + a * 8192 + 256, v1); }
    }
    fence_async_smem();
    bar_sync(1 + wg, 128);
    if ((tid & 127) == 0) {
      tma_store3(&tmImg, sb + wg * 24576 + a * 8192, type == 2 ? 96 : 0, rb * 16 + wg * 8, slot);
      asm volatile("cp.async.bulk.commit_group;" ::: "memory");
    }
    unsigned char* tp = g_img + (size_t)(slot + c) * HS + (rb * 16 + warp * 2) * 640 + 256;
    if (type == 0) {
      *(uint32_t*)(tp + g * 4) = t0;
      *(uint32_t*)(tp + 640 + g * 4) = t1;
    } else {
      tp += g * 16 + (type == 2 ? 8 : 0);
      *(uint2*)tp = make_uint2(t0, (type == 1 && poly0) ? 0x26801800u : 0x00003C00u);
      *(uint2*)(tp + 640) = make_uint2(t1, (type == 1 && poly1) ? 0x26801800u : 0x00003C00u);
    }
    if (type == 1) {
      float n[2][4];
#pragma unroll
      for (int r = 0; r < 2; r++) {
        float q[9];
#pragma unroll
        for (int b = 0; b < 9; b++) { const int i = 4 * (9 * a + b) + 2 * r; q[b] = acc[i] * acc[i] + acc[i + 1] * acc[i + 1]; }
        n[r][0] = q[0] + q[1] + (c < 1 ? q[2] : 0.f);
        n[r][1] = q[3] + (c < 1 ? 0.f : q[2]) + (c < 2 ? q[4] : 0.f);
        n[r][2] = q[5] + (c < 2 ? 0.f : q[4]) + (c < 3 ? q[6] : 0.f);
        n[r][3] = q[7] + q[8] + (c < 3 ? 0.f : q[6]);
      }
      uint32_t m = 0;
#pragma unroll
      for (int r = 0; r < 2; r++) {
        const bool u = c & 1, v = c & 2;
        float a0 = (u ? n[r][2] : n[r][0]) + __shfl_xor_sync(~0u, u ? n[r][0] : n[r][2], 1);
        float a1 = (u ? n[r][3] : n[r][1]) + __shfl_xor_sync(~0u, u ? n[r][1] : n[r][3], 1);
        float t = (v ? a1 : a0) + __shfl_xor_sync(~0u, v ? a0 : a1, 2);
        m = max(m, __float_as_uint(t));
      }
      m = max(m, __shfl_xor_sync(~0u, m, 4));
      m = max(m, __shfl_xor_sync(~0u, m, 8));
      m = max(m, __shfl_xor_sync(~0u, m, 16));
      if (g == 0) g_knorm[(slot - 32 + 2 * (c & 1) + (c >> 1)) * 128 + rb * 8 + warp] = __uint_as_float(m);
    }
  }
  if ((tid & 127) == 0) asm volatile("cp.async.bulk.wait_group 0;" ::: "memory");
  if (tid == 0) STAMP(0, blockIdx.x, 3);
}

DEVI uint32_t ex2_mufu(uint32_t x) { uint32_t y; asm("ex2.approx.f16x2 %0, %1;" : "=r"(y) : "r"(x)); return y; }
DEVI uint32_t hfma2(uint32_t a, uint32_t b, uint32_t c) { uint32_t d; asm("fma.rn.f16x2 %0, %1, %2, %3;" : "=r"(d) : "r"(a), "r"(b), "r"(c)); return d; }
DEVI uint32_t hfma2r(uint32_t a, uint32_t b, uint32_t c) { uint32_t d; asm("fma.rn.relu.f16x2 %0, %1, %2, %3;" : "=r"(d) : "r"(a), "r"(b), "r"(c)); return d; }
DEVI uint32_t ex2_fma(uint32_t y, uint32_t c3) {
  const uint32_t t = hfma2r(y, 0x02000200u, 0u);
  const uint32_t f = hfma2(t, 0xF800F800u, y);
  uint32_t p = hfma2(f, c3, 0x47c047c0u);
  p = hfma2(p, f, 0x298c298cu);
  p = hfma2r(p, f, 0x08000800u);
  return __funnelshift_l(t, t, 10) + p;
}

constexpr int A_SLOT = 20480, A_BARS = 4 * A_SLOT, A_SMEM = A_BARS + 64;

__device__ __noinline__ void attn_exact(const bf16* __restrict__ X, const bf16* __restrict__ W, int h, int qb, uint32_t mask, unsigned char* smem) {
  uint32_t* kv = (uint32_t*)smem;
  const int tid = threadIdx.x, slab = tid >> 4;
  const int qt = (slab >> 4) * 16 + qb * 4 + ((slab >> 2) & 3), row = qt * 64 + (slab & 3) * 16 + (tid & 15);
  float q[18], o[18];
#pragma unroll
  for (int i = 0; i < 18; i++) { q[i] = 0.f; o[i] = 0.f; }
#pragma unroll 1
  for (int d = 0; d < DM; d++) {
    const float x = __bfloat162float(X[row * DM + d]);
    const uint32_t* wq = (const uint32_t*)(W + d * 1728 + h * 18);
#pragma unroll
    for (int i = 0; i < 9; i++) { const uint32_t u = wq[i]; q[2 * i] += x * bf_lo(u); q[2 * i + 1] += x * bf_hi(u); }
  }
#pragma unroll
  for (int i = 0; i < 18; i++) q[i] = bf_round(q[i]);
  float m = -INFINITY, l = 0.f;
#pragma unroll 1
  for (int half = 0; half < 2; half++) {
    __syncthreads();
#pragma unroll 1
    for (int kp = tid; kp < 2048; kp += 512) {
      const int key = kp >> 1, part = kp & 1;
      float a[18];
#pragma unroll
      for (int i = 0; i < 18; i++) a[i] = 0.f;
#pragma unroll 1
      for (int d = 0; d < DM; d++) {
        const float x = __bfloat162float(X[(half * 1024 + key) * DM + d]);
        const uint32_t* w = (const uint32_t*)(W + d * 1728 + 576 + part * 576 + h * 18);
#pragma unroll
        for (int i = 0; i < 9; i++) { const uint32_t u = w[i]; a[2 * i] += x * bf_lo(u); a[2 * i + 1] += x * bf_hi(u); }
      }
#pragma unroll
      for (int i = 0; i < 9; i++) kv[key * 18 + part * 9 + i] = pack_b2(a[2 * i], a[2 * i + 1]);
    }
    __syncthreads();
#pragma unroll 1
    for (int key = 0; key < 1024; key++) {
      float s = 0.f;
#pragma unroll
      for (int i = 0; i < 9; i++) { const uint32_t u = kv[key * 18 + i]; s += q[2 * i] * bf_lo(u) + q[2 * i + 1] * bf_hi(u); }
      s = bf_round(bf_round(s) * 0.23570226f);
      const float mn = fmaxf(m, s), al = (m == mn) ? 1.f : expf(m - mn), p = expf(s - mn);
      m = mn;
      l = l * al + p;
#pragma unroll
      for (int i = 0; i < 9; i++) { const uint32_t u = kv[key * 18 + 9 + i]; o[2 * i] = o[2 * i] * al + p * bf_lo(u); o[2 * i + 1] = o[2 * i + 1] * al + p * bf_hi(u); }
    }
  }
  const bool mine = (mask >> slab) & 1;
  if (mine) {
    const float inv = 1.f / l;
#pragma unroll
    for (int i = 0; i < 9; i++) *(uint32_t*)(g_O + row * DM + h * 18 + 2 * i) = pack_b2(o[2 * i] * inv, o[2 * i + 1] * inv);
  }
  __syncwarp();
  if (mine && (tid & 15) == 0) red_release(g_cnt + (CNT_O + qt) * 32, 1);
}

__global__ void __launch_bounds__(640, 1)
attn_kernel(const bf16* __restrict__ X, const bf16* __restrict__ W, uint32_t c3) {
  extern __shared__ __align__(1024) unsigned char smem[];
  const int tid = threadIdx.x, warp = tid >> 5, lane = tid & 31;
  const int h = blockIdx.x >> 2, qb = blockIdx.x & 3;
  const uint32_t sb = s2u(smem), bars = sb + A_BARS;
  uint32_t* sm32 = (uint32_t*)(smem + A_BARS + 32);
  if (tid == 0) {
    STAMP(1, blockIdx.x, 0);
#pragma unroll
    for (int i = 0; i < 4; i++) { mbar_init(bars + 8 * i, 1); sm32[i] = 0; }
    sm32[4] = 0;
    fence_mbar_init();
  }
  __syncthreads();
  pdl_wait();
  const unsigned char* kvimg = g_img + (size_t)(32 + h) * HS;
  if (tid < 4) {
    mbar_expect(bars + 8 * tid, A_SLOT);
    bulk_load(sb + tid * A_SLOT, kvimg + tid * A_SLOT, A_SLOT, bars + 8 * tid);
  }
  if (tid == 0) { STAMP(1, blockIdx.x, 1); __threadfence(); pdl_launch(); }
  const uint64_t dk0 = mkdesc(sb, 128, 640, 0), dv0 = mkdesc(sb + 256, 640, 128, 0);
#pragma unroll 1
  for (int pass = 0; pass < 2; pass++) {
    const int g = lane >> 2, c = lane & 3;
    const int qt = pass * 16 + qb * 4 + (warp >> 2), grp = qt * 8 + (warp & 3) * 2;
    const unsigned char* qp = g_img + (size_t)h * HS + grp * 640;
    uint32_t q0 = *(const uint32_t*)(qp + lane * 4), q1 = *(const uint32_t*)(qp + 640 + lane * 4);
    uint32_t q2 = *(const uint32_t*)(qp + 128 + lane * 4), q3 = *(const uint32_t*)(qp + 768 + lane * 4);
    uint32_t q4 = 0, q5 = 0;
    if (c == 0) { q4 = *(const uint32_t*)(qp + 256 + g * 4); q5 = *(const uint32_t*)(qp + 896 + g * 4); }
    uint32_t chk;
    {
      const uint4 v = *(const uint4*)(g_knorm + h * 128 + lane * 4);
      const float kmax = sqrtf(__uint_as_float(__reduce_max_sync(~0u, max(max(v.x, v.y), max(v.z, v.w)))));
      float2 a = __half22float2(*(__half2*)&q0), b = __half22float2(*(__half2*)&q2), e = __half22float2(*(__half2*)&q4);
      float n0 = a.x * a.x + a.y * a.y + b.x * b.x + b.y * b.y + e.x * e.x + e.y * e.y;
      a = __half22float2(*(__half2*)&q1); b = __half22float2(*(__half2*)&q3); e = __half22float2(*(__half2*)&q5);
      float n1 = a.x * a.x + a.y * a.y + b.x * b.x + b.y * b.y + e.x * e.x + e.y * e.y;
      n0 += __shfl_xor_sync(~0u, n0, 1); n1 += __shfl_xor_sync(~0u, n1, 1);
      n0 += __shfl_xor_sync(~0u, n0, 2); n1 += __shfl_xor_sync(~0u, n1, 2);
      const float b0 = sqrtf(n0) * kmax * 1.002f + 0.004f, b1 = sqrtf(n1) * kmax * 1.002f + 0.004f;
      chk = !(kmax <= 1024.f && n0 <= 1024.f && n1 <= 1024.f && b0 <= 64.f && b1 <= 64.f);
      chk |= (b0 > 14.375f ? 2 : 0) | (b1 > 14.375f ? 4 : 0);
      const float m0 = fmaxf(b0 - 15.25f, fminf(0.f, 13.5f - b0)), m1 = fmaxf(b1 - 15.25f, fminf(0.f, 13.5f - b1));
      if (c == 1) { q4 = pack_h2(-m0, 1.f); q5 = pack_h2(-m1, 1.f); }
    }
    float o[12];
#pragma unroll
    for (int i = 0; i < 12; i++) o[i] = 0.f;
#pragma unroll 1
    for (int i = 0; i < 16; i++) {
      const int ch = pass ? 7 - (i >> 1) : (i >> 1), slot = ch & 3;
      const uint32_t off = slot * 1280 + (i & 1) * 640;
      uint32_t s[32];
      if (!(i & 1) && (pass == 0 || ch < 4)) mbar_wait(bars + 8 * slot, pass ? 0 : ch >> 2);
      wg_fence();
      qk_n128_z(s, q0, q1, q2, q3, dk0 + off);
      qk_n128(s, q4, q5, 0u, 0u, dk0 + off + 16);
      wg_commit();
      wg_wait<0>();
#pragma unroll
      for (int k = 0; k < 32; k++) s[k] = ((PM >> (k >> 1)) & 1) ? ex2_fma(s[k], c3) : ex2_mufu(s[k]);
      wg_fence();
#pragma unroll
      for (int k = 0; k < 8; k++) pv_n24(o, s[4 * k], s[4 * k + 1], s[4 * k + 2], s[4 * k + 3], dv0 + off + k * 80);
      wg_commit();
      wg_wait<0>();
      if ((i & 1) && ((ch < 4) == (pass == 0))) {
        if (lane == 0 && (atomicAdd(sm32 + slot, 1) & 15) == 15) {
          mbar_expect(bars + 8 * slot, A_SLOT);
          bulk_load(sb + slot * A_SLOT, kvimg + (ch ^ 4) * A_SLOT, A_SLOT, bars + 8 * slot);
        }
        __syncwarp();
      }
    }
    const float l0 = __shfl_sync(~0u, o[0], lane | 3), l1 = __shfl_sync(~0u, o[2], lane | 3);
    uint32_t bad = (chk & 1) | !(l0 >= ((chk & 2) ? 512.f : 1e-30f) && l0 <= 3e38f && l1 >= ((chk & 4) ? 512.f : 1e-30f) && l1 <= 3e38f);
    const float i0 = 1.f / l0, i1 = 1.f / l1;
    if (c != 2) { o[0] = 0.f; o[1] = 0.f; o[2] = 0.f; o[3] = 0.f; }
    uint32_t omax = 0;
#pragma unroll
    for (int i = 0; i < 12; i++) { o[i] *= (i & 2) ? i1 : i0; omax = max(omax, __float_as_uint(o[i]) & 0x7FFFFFFFu); }
    omax = __reduce_max_sync(~0u, omax);
    bad = __reduce_or_sync(~0u, bad) | (omax >= 0x7F800000u) | (omax < 0x3A800000u);
    if (!bad) {
      bf16* op = g_O + (grp * 8 + g) * DM + h * 18;
      *(uint32_t*)(op + 2 * c) = pack_b2(o[4], o[5]);
      *(uint32_t*)(op + 8 + 2 * c) = pack_b2(o[8], o[9]);
      *(uint32_t*)(op + 8 * DM + 2 * c) = pack_b2(o[6], o[7]);
      *(uint32_t*)(op + 8 * DM + 8 + 2 * c) = pack_b2(o[10], o[11]);
      if (c == 2) { *(uint32_t*)(op + 16) = pack_b2(o[0], o[1]); *(uint32_t*)(op + 8 * DM + 16) = pack_b2(o[2], o[3]); }
      __syncwarp();
      if (lane == 0) red_release(g_cnt + (CNT_O + qt) * 32, 1);
    } else if (lane == 0) {
      atomicOr(sm32 + 4, 1u << (pass * 16 + warp));
    }
    __syncwarp();
    if (tid == 0) { STAMP(1, blockIdx.x, 2 + pass); CSTAMP(1, blockIdx.x + 128, 2 + pass); }
  }
  __syncthreads();
  const uint32_t mask = *(volatile uint32_t*)(sm32 + 4);
  if (mask) attn_exact(X, W, h, qb, mask, smem);
}

constexpr int NS = 5, S_STAGE = 26624, S_BARS = NS * S_STAGE, S_SMEM = S_BARS + 128;
constexpr uint32_t T_OUT = 288, T_WO = 416, T_DYN = 533, T_END = 650;
DEVI float2 cmul(float2 a, float2 b) { return make_float2(a.x * b.x - a.y * b.y, a.x * b.y + a.y * b.x); }
DEVI float2 cfma(float2 a, float2 b, float2 c) { return make_float2(fmaf(a.x, b.x, fmaf(-a.y, b.y, c.x)), fmaf(a.x, b.y, fmaf(a.y, b.x, c.y))); }

struct Maps { CUtensorMap B, X, H, Cre, Cim, Wo, O; };
struct Item { int type, u, v; };
DEVI Item decode(uint32_t t) {
  Item w;
  if (t < T_OUT) { w.type = 0; w.u = t / 18; w.v = t - w.u * 18; }
  else if (t < T_WO) { w.type = 1; w.u = (t - T_OUT) >> 2; w.v = (t - T_OUT) & 3; }
  else if (t < T_END) {
    const int i = t - T_WO, half = i >= 117, r = i - 117 * half, tb = r / 9;
    w.type = 2; w.u = half * 1024 + min(tb * 80, 944); w.v = r - tb * 9;
  } else { w.type = 3; w.u = 0; w.v = 0; }
  return w;
}
DEVI void issue_free(const Maps& m, const Item& w, int k, uint32_t st, uint32_t bar) {
  if (w.type == 0) {
    mbar_expect(bar, 24576);
    tma4(st, &m.B, k * 64, 0, 0, w.v * 4, bar);
    tma5(st + 8192, &m.X, k * 64, 0, 0, 0, w.u, bar);
  } else if (w.type == 1) {
    mbar_expect(bar, 26624);
    tma2(st + 8192, k < 9 ? &m.Cre : &m.Cim, (k < 9 ? k : k - 9) * 64, w.v * 144, bar);
  } else if (w.type == 2) {
    mbar_expect(bar, 18432);
    tma2(st, &m.Wo, w.v * 64, k * 64, bar);
  }
}
DEVI void issue_dep(const Maps& m, const Item& w, int k, uint32_t st, uint32_t bar) {
  if (w.type == 1) tma2(st, &m.H, w.u * 64, k * 64, bar);
  else if (w.type == 2) tma2(st + 8192, &m.O, k * 64, w.u, bar);
}

struct Pipe { uint32_t sb, bars, st, ph; };
DEVI uint32_t prev_stage(uint32_t s, int d) { return s >= (uint32_t)d ? s - d : s + NS - d; }

template <int TYPE, int NK, int NACC>
DEVI void mainloop(float (&acc)[NACC], Pipe& p, const Maps& m, const Item& w, const Item& nx) {
  const int tid = threadIdx.x;
#pragma unroll
  for (int i = 0; i < NACC; i++) acc[i] = 0.f;
  auto refill = [&](int kb, int d) {
    const uint32_t s = prev_stage(p.st, d), ph = p.ph ^ (p.st < (uint32_t)d);
    mbar_wait(p.bars + 8 * (NS + s), ph);
    const uint32_t st = p.sb + s * S_STAGE, bar = p.bars + 8 * s;
    if (kb + NS < NK) { issue_free(m, w, kb + NS, st, bar); issue_dep(m, w, kb + NS, st, bar); }
    else issue_free(m, nx, kb + NS - NK, st, bar);
  };
#pragma unroll 1
  for (int kb = 0; kb < NK; kb++) {
    const uint64_t dA = mkdesc(p.sb + p.st * S_STAGE, 16, 1024, 1), dB = dA + 512;
    mbar_wait(p.bars + 8 * p.st, p.ph);
    wg_fence();
#pragma unroll
    for (int ks = 0; ks < 4; ks++) {
      if constexpr (TYPE == 0) mma_n128(acc, dA + ks * 2, dB + ks * 2);
      else if constexpr (TYPE == 1) mma_n144_ta(acc, dA + ks * 128, dB + ks * 2);
      else mma_n80_ta(acc, dA + ks * 128, dB + ks * 2);
    }
    wg_commit();
    if (kb >= 2 && tid == 0) refill(kb - 2, 2);
    __syncwarp();
    if (kb >= 1) {
      wg_wait<1>();
      if ((tid & 31) == 0) mbar_arrive(p.bars + 8 * (NS + prev_stage(p.st, 1)));
    }
    if (++p.st == NS) { p.st = 0; p.ph ^= 1; }
  }
  wg_wait<0>();
  if ((tid & 31) == 0) mbar_arrive(p.bars + 8 * (NS + prev_stage(p.st, 1)));
  if (tid == 0) { refill(NK - 2, 2); refill(NK - 1, 1); }
  __syncwarp();
}

template <bool SWAP>
__global__ void __launch_bounds__(128, 4)
worker_kernel(const __grid_constant__ Maps m, const bf16* __restrict__ x, const bf16* __restrict__ lre, const bf16* __restrict__ lim,
              const bf16* __restrict__ ldt, const bf16* __restrict__ dskip, float* __restrict__ out) {
  extern __shared__ __align__(1024) unsigned char smem[];
  const int tid = threadIdx.x, warp = tid >> 5, lane = tid & 31, g = lane >> 2, c = lane & 3;
  Pipe pp;
  pp.sb = s2u(smem); pp.bars = pp.sb + S_BARS; pp.st = 0; pp.ph = 0;
  volatile uint32_t* stick = (volatile uint32_t*)(smem + S_BARS + 16 * NS);
  const uint32_t last = blockIdx.x < 117 ? T_DYN + blockIdx.x : T_END;
  if (tid == 0) {
    STAMP(2, blockIdx.x, 0);
    uint32_t t = atomicAdd(g_cnt + CNT_TICKET * 32, 1);
#pragma unroll
    for (int i = 0; i < NS; i++) { mbar_init(pp.bars + 8 * i, 1); mbar_init(pp.bars + 8 * (NS + i), 4); }
    fence_mbar_init();
    if (t >= T_DYN) t = last;
    stick[0] = t;
    const Item w = decode(t);
#pragma unroll 1
    for (int k = 0; k < NS; k++) issue_free(m, w, k, pp.sb + k * S_STAGE, pp.bars + 8 * k);
  }
  __syncthreads();
  int nt = 0;
#pragma unroll 1
  while (true) {
    const uint32_t ticket = stick[nt & 1];
    if (ticket >= T_END) break;
    const Item w = decode(ticket);
    Item nx;
    nx.type = 3; nx.u = 0; nx.v = 0;
    if (tid == 0) {
      uint32_t next = T_END;
      if (ticket < T_DYN) { next = atomicAdd(g_cnt + CNT_TICKET * 32, 1); if (next >= T_DYN) next = last; }
      if (w.type != 0) {
        if (w.type == 1) wait_count(g_cnt + (CNT_H + (w.u >> 1)) * 32, 72);
        else { wait_count(g_cnt + (CNT_O + (w.u >> 6)) * 32, 128); wait_count(g_cnt + (CNT_O + (w.u >> 6) + 1) * 32, 128); }
        fence_async_gmem();
        if (ticket >= T_DYN) STAMP(3, blockIdx.x, 0);
        uint32_t s = pp.st;
#pragma unroll 1
        for (int k = 0; k < NS; k++) { issue_dep(m, w, k, pp.sb + s * S_STAGE, pp.bars + 8 * s); if (++s == NS) s = 0; }
      }
      stick[(nt + 1) & 1] = next;
      nx = decode(next);
    }
    __syncwarp();
    if (w.type == 0) {
      const int chunk = w.u, p = w.v * 32 + warp * 8 + g;
      float2 lam, coef;
      {
        const float dt = bf_round(expf(__bfloat162float(ldt[p]))), re = __bfloat162float(lre[p]), im = __bfloat162float(lim[p]);
        const float e = expf(dt * re);
        float sn, cs;
        sincosf(dt * im, &sn, &cs);
        lam = make_float2(e * cs, e * sn);
        const float r = 2.f / (re * re + im * im);
        coef = make_float2(((lam.x - 1.f) * re + lam.y * im) * r, (lam.y * re - (lam.x - 1.f) * im) * r);
      }
      float acc[64];
      mainloop<0, 9>(acc, pp, m, w, nx);
      constexpr int RE = SWAP ? 2 : 0, IM = SWAP ? 0 : 2;
      float2 a = make_float2(0.f, 0.f);
#pragma unroll
      for (int t = 0; t < 32; t++) a = cfma(lam, a, make_float2(acc[4 * (t >> 1) + RE + (t & 1)], acc[4 * (t >> 1) + IM + (t & 1)]));
      float2 l32 = lam;
#pragma unroll
      for (int i = 0; i < 5; i++) l32 = cmul(l32, l32);
      const float2 l64 = cmul(l32, l32), l128 = cmul(l64, l64), l256 = cmul(l128, l128), l512 = cmul(l256, l256);
      float2 u = make_float2(__shfl_up_sync(~0u, a.x, 1), __shfl_up_sync(~0u, a.y, 1));
      if (c >= 1) a = cfma(l32, u, a);
      u = make_float2(__shfl_up_sync(~0u, a.x, 2), __shfl_up_sync(~0u, a.y, 2));
      if (c >= 2) a = cfma(l64, u, a);
      if (c == 3 && chunk < 15) {
        unsigned long long v = ((unsigned long long)__float_as_uint(a.y) << 32) | __float_as_uint(a.x);
        if (v == AGG_EMPTY) v = 0x7FFFFFFF7FFFFFFFull;
        asm volatile("st.relaxed.gpu.global.u64 [%0], %1;" ::"l"(g_agg + chunk * DM + p), "l"(v) : "memory");
      }
      float2 st = make_float2(__shfl_up_sync(~0u, a.x, 1), __shfl_up_sync(~0u, a.y, 1));
      if (c == 0) st = make_float2(0.f, 0.f);
      float2 hin = make_float2(0.f, 0.f);
      {
        unsigned long long v[4];
        int n = 0;
        bool miss;
#pragma unroll 1
        do {
          miss = false;
#pragma unroll
          for (int i = 0; i < 4; i++) {
            const int cc = chunk - 1 - c - 4 * i;
            v[i] = 0;
            if (cc >= 0) asm volatile("ld.relaxed.gpu.global.u64 %0, [%1];" : "=l"(v[i]) : "l"(g_agg + cc * DM + p) : "memory");
          }
#pragma unroll
          for (int i = 0; i < 4; i++) miss |= v[i] == AGG_EMPTY;
          if (++n > (1 << 23)) __trap();
        } while (__any_sync(~0u, miss));
#pragma unroll
        for (int i = 3; i >= 0; i--) hin = cfma(l512, hin, make_float2(__uint_as_float((uint32_t)v[i]), __uint_as_float((uint32_t)(v[i] >> 32))));
        const float2 f = c == 0 ? make_float2(1.f, 0.f) : (c == 1 ? l128 : (c == 2 ? l256 : cmul(l128, l256)));
        hin = cmul(hin, f);
        hin.x += __shfl_xor_sync(~0u, hin.x, 1); hin.y += __shfl_xor_sync(~0u, hin.y, 1);
        hin.x += __shfl_xor_sync(~0u, hin.x, 2); hin.y += __shfl_xor_sync(~0u, hin.y, 2);
        const float2 f2 = c == 0 ? make_float2(1.f, 0.f) : (c == 1 ? l32 : (c == 2 ? l64 : cmul(l32, l64)));
        st = cfma(f2, hin, st);
      }
      bf16* hp = g_HT + (size_t)p * HT_LD + chunk * 128 + c * 32;
#pragma unroll
      for (int v = 0; v < 4; v++) {
        uint32_t wr[4], wi[4];
#pragma unroll
        for (int i = 0; i < 4; i++) {
          const int jj = 4 * (4 * v + i);
          st = cfma(lam, st, make_float2(acc[jj + RE], acc[jj + IM]));
          const float r0 = coef.x * st.x - coef.y * st.y, m0 = -coef.x * st.y - coef.y * st.x;
          st = cfma(lam, st, make_float2(acc[jj + RE + 1], acc[jj + IM + 1]));
          const float r1 = coef.x * st.x - coef.y * st.y, m1 = -coef.x * st.y - coef.y * st.x;
          wr[i] = pack_b2(r0, r1); wi[i] = pack_b2(m0, m1);
        }
        *(uint4*)(hp + 8 * v) = make_uint4(wr[0], wr[1], wr[2], wr[3]);
        *(uint4*)(hp + DM * HT_LD + 8 * v) = make_uint4(wi[0], wi[1], wi[2], wi[3]);
      }
      __syncwarp();
      if (lane == 0) red_release(g_cnt + (CNT_H + chunk) * 32, 1);
    } else if (w.type == 1) {
      float acc[72];
      mainloop<1, 18>(acc, pp, m, w, nx);
      const int row = w.u * 64 + warp * 16 + g, col = w.v * 144 + 2 * c;
      const bf16* xp = x + row * DM + col;
      float* op = out + (size_t)row * 1152 + col;
#pragma unroll
      for (int b = 0; b < 18; b++) {
        const uint32_t d = *(const uint32_t*)(dskip + col + 8 * b), x0 = *(const uint32_t*)(xp + 8 * b), x1 = *(const uint32_t*)(xp + 8 * DM + 8 * b);
        const uint32_t k0 = pack_b2(bf_lo(x0) * bf_lo(d), bf_hi(x0) * bf_hi(d)), k1 = pack_b2(bf_lo(x1) * bf_lo(d), bf_hi(x1) * bf_hi(d));
        *(float2*)(op + 8 * b) = make_float2(acc[4 * b] + bf_lo(k0), acc[4 * b + 1] + bf_hi(k0));
        *(float2*)(op + 8 * 1152 + 8 * b) = make_float2(acc[4 * b + 2] + bf_lo(k1), acc[4 * b + 3] + bf_hi(k1));
      }
    } else {
      float acc[40];
      mainloop<2, 9>(acc, pp, m, w, nx);
      if (tid == 0 && ticket >= T_DYN) STAMP(3, blockIdx.x, 1);
      float* op = out + (size_t)(w.u + 2 * c) * 1152 + 576 + w.v * 64 + warp * 16 + g;
#pragma unroll
      for (int b = 0; b < 10; b++) {
        op[(8 * b) * 1152] = acc[4 * b];
        op[(8 * b + 1) * 1152] = acc[4 * b + 1];
        op[(8 * b) * 1152 + 8] = acc[4 * b + 2];
        op[(8 * b + 1) * 1152 + 8] = acc[4 * b + 3];
      }
    }
    __syncthreads();
    nt++;
    if (tid == 0 && nt < 7) STAMP(2, blockIdx.x, nt);
  }
  if (tid == 0) STAMP(2, blockIdx.x, 7);
  if (tid == 0 && blockIdx.x == 0) pdl_wait();
}

typedef CUresult (*EncodeFn)(CUtensorMap*, CUtensorMapDataType, cuuint32_t, void*, const cuuint64_t*, const cuuint64_t*,
                             const cuuint32_t*, const cuuint32_t*, CUtensorMapInterleave, CUtensorMapSwizzle,
                             CUtensorMapL2promotion, CUtensorMapFloatOOBfill);

struct Setup {
  CUtensorMap xB, img;
  Maps m;
  const void* key[12];
  bool swap, ok;
};

bool encode(EncodeFn fn, CUtensorMap* m, const void* base, int rank, const cuuint64_t* dims, const cuuint64_t* strides,
            const cuuint32_t* box, CUtensorMapSwizzle sw, CUtensorMapDataType dt = CU_TENSOR_MAP_DATA_TYPE_BFLOAT16) {
  const cuuint32_t es[5] = {1, 1, 1, 1, 1};
  return fn(m, dt, rank, (void*)base, dims, strides, box, es, CU_TENSOR_MAP_INTERLEAVE_NONE, sw,
            CU_TENSOR_MAP_L2_PROMOTION_L2_256B, CU_TENSOR_MAP_FLOAT_OOB_FILL_NONE) == CUDA_SUCCESS;
}
bool encode2(EncodeFn fn, CUtensorMap* m, const void* base, uint64_t cols, uint64_t rows, uint64_t ld, uint32_t br) {
  const cuuint64_t d[2] = {cols, rows}, s[1] = {ld * 2};
  const cuuint32_t b[2] = {64, br};
  return encode(fn, m, base, 2, d, s, b, CU_TENSOR_MAP_SWIZZLE_128B);
}

template <typename... KA, typename... A>
void launch(void (*k)(KA...), int grid, int block, int smem, bool pdl, A... args) {
  cudaLaunchConfig_t cfg = {};
  cfg.gridDim = dim3(grid); cfg.blockDim = dim3(block); cfg.dynamicSmemBytes = smem; cfg.stream = cudaStreamPerThread;
  cudaLaunchAttribute at[1];
  at[0].id = cudaLaunchAttributeProgrammaticStreamSerialization;
  at[0].val.programmaticStreamSerializationAllowed = 1;
  cfg.attrs = at; cfg.numAttrs = pdl ? 1 : 0;
  cudaLaunchKernelEx(&cfg, k, KA(args)...);
}
template <typename K> void set_smem(K k, int bytes) {
  cudaFuncSetAttribute(k, cudaFuncAttributeMaxDynamicSharedMemorySize, bytes);
  cudaFuncSetAttribute(k, cudaFuncAttributePreferredSharedMemoryCarveout, 100);
}

}

extern "C" void kernel_launch(void* const* d_in, const int* in_sizes, int n_in, void* d_out, int out_size) {
  static Setup S = {};
  bool same = S.ok;
  for (int i = 0; i < 12; i++) same = same && S.key[i] == d_in[i];
  if (!same) {
    void* fp = nullptr;
    cudaDriverEntryPointQueryResult qr;
    cudaGetDriverEntryPoint("cuTensorMapEncodeTiled", &fp, cudaEnableDefault, &qr);
    EncodeFn fn = (EncodeFn)fp;
    void *pO, *pH, *pI;
    cudaGetSymbolAddress(&pO, g_O);
    cudaGetSymbolAddress(&pH, g_HT);
    cudaGetSymbolAddress(&pI, g_img);
    bool ok = fn != nullptr;
    ok = ok && encode2(fn, &S.xB, d_in[9], DM, SEQ, DM, 128);
    ok = ok && encode2(fn, &S.m.O, pO, DM, SEQ, DM, 80);
    ok = ok && encode2(fn, &S.m.Wo, d_in[11], DM, DM, DM, 64);
    ok = ok && encode2(fn, &S.m.H, pH, SEQ, 2 * DM, HT_LD, 64);
    ok = ok && encode2(fn, &S.m.Cre, d_in[5], DM, DM, DM, 144);
    ok = ok && encode2(fn, &S.m.Cim, d_in[6], DM, DM, DM, 144);
    {
      const cuuint64_t d[3] = {160, 256, 64}, s[2] = {640, HS};
      const cuuint32_t b[3] = {64, 8, 4};
      ok = ok && encode(fn, &S.img, pI, 3, d, s, b, CU_TENSOR_MAP_SWIZZLE_NONE, CU_TENSOR_MAP_DATA_TYPE_UINT32);
    }
    {
      const char *re = (const char*)d_in[3], *im = (const char*)d_in[4];
      S.swap = im < re;
      const cuuint64_t d[4] = {DM, 8, 2, 72}, s[3] = {DM * 2, (cuuint64_t)(S.swap ? re - im : im - re), 8 * DM * 2};
      const cuuint32_t b[4] = {64, 8, 2, 4};
      ok = ok && encode(fn, &S.m.B, S.swap ? im : re, 4, d, s, b, CU_TENSOR_MAP_SWIZZLE_128B);
    }
    {
      const cuuint64_t d[5] = {DM, 2, 4, 16, 16}, s[4] = {DM * 2, 32 * DM * 2, 2 * DM * 2, 128 * DM * 2};
      const cuuint32_t b[5] = {64, 2, 4, 16, 1};
      ok = ok && encode(fn, &S.m.X, d_in[0], 5, d, s, b, CU_TENSOR_MAP_SWIZZLE_128B);
    }
    set_smem(qkv_kernel, Q_SMEM);
    set_smem(attn_kernel, A_SMEM);
    set_smem(worker_kernel<false>, S_SMEM);
    set_smem(worker_kernel<true>, S_SMEM);
    for (int i = 0; i < 12; i++) S.key[i] = d_in[i];
    S.ok = ok;
    if (!ok) return;
  }
  PrefetchList pf;
  const int order[6] = {0, 3, 4, 5, 6, 11};
  for (int i = 0; i < 6; i++) pf.p[i] = (const unsigned char*)d_in[order[i]];
  const bf16 *Bx = (const bf16*)d_in[9], *Wq = (const bf16*)d_in[10];
  launch(qkv_kernel, 128, 256, Q_SMEM, false, S.xB, S.img, Wq, pf);
  launch(attn_kernel, 128, 512, A_SMEM, true, Bx, Wq, 0x630d630du);
  launch(S.swap ? worker_kernel<true> : worker_kernel<false>, 132, 128, S_SMEM, true, S.m, (const bf16*)d_in[0], (const bf16*)d_in[1],
         (const bf16*)d_in[2], (const bf16*)d_in[7], (const bf16*)d_in[8], (float*)d_out);
}
```

```cpp
#include <cuda_runtime.h>
#include <cuda.h>
#include <cuda_bf16.h>
#include <cuda_fp16.h>
#include <stdint.h>

namespace {

#define DEVI __device__ __forceinline__
typedef __nv_bfloat16 bf16;

constexpr int SEQ = 2048, DM = 576;
constexpr int HQ = 128 * 640, HS = 8 * 16384, HT = 8192;
constexpr uint32_t PM = 0x6b6b;

__device__ __align__(1024) unsigned char g_q[32 * HQ], g_kv[32 * HS], g_tail[64 * HT];
__device__ __align__(128) unsigned g_knorm[32 * 128];
__device__ __align__(1024) unsigned char g_O[SEQ * DM * 2];
constexpr int O_BLK = SEQ * 128, HT_LD = 2112;
constexpr uint32_t O_EMPTY = 0xFFFFFFFFu;
__device__ __align__(128) bf16 g_HT[2 * DM * HT_LD];
__device__ __align__(128) uint64_t g_agg[20 * DM];
__device__ __align__(128) float4 g_tab[DM * 16];
__device__ __align__(128) unsigned g_flag[16 * 32];
__device__ __align__(128) unsigned g_cnt[32 * 49];
constexpr int CNT_H = 0, CNT_O = 16, CNT_Q = 32, CNT_SIDE = 48;
constexpr unsigned AGG_EMPTY = 0xFFFFFFFFu;

DEVI uint32_t s2u(const void* p) { return (uint32_t)__cvta_generic_to_shared(p); }
DEVI void mbar_init(uint32_t b, int c) { asm volatile("mbarrier.init.shared::cta.b64 [%0], %1;" ::"r"(b), "r"(c) : "memory"); }
DEVI void mbar_expect(uint32_t b, uint32_t bytes) { asm volatile("mbarrier.arrive.expect_tx.shared::cta.b64 _, [%0], %1;" ::"r"(b), "r"(bytes) : "memory"); }
DEVI void mbar_arrive(uint32_t b) { asm volatile("mbarrier.arrive.shared::cta.b64 _, [%0];" ::"r"(b) : "memory"); }
DEVI void mbar_arrive_n(uint32_t b, uint32_t n) { asm volatile("mbarrier.arrive.shared::cta.b64 _, [%0], %1;" ::"r"(b), "r"(n) : "memory"); }
DEVI bool mbar_try(uint32_t b, uint32_t ph) {
  uint32_t r;
  asm volatile("{\n.reg .pred p;\nmbarrier.try_wait.parity.shared::cta.b64 p, [%1], %2;\nselp.u32 %0, 1, 0, p;\n}" : "=r"(r) : "r"(b), "r"(ph) : "memory");
  return r;
}
DEVI bool mbar_try_long(uint32_t b, uint32_t ph) {
  uint32_t r;
  asm volatile("{\n.reg .pred p;\nmbarrier.try_wait.parity.shared::cta.b64 p, [%1], %2, %3;\nselp.u32 %0, 1, 0, p;\n}" : "=r"(r) : "r"(b), "r"(ph), "n"(50000) : "memory");
  return r;
}
DEVI void mbar_wait(uint32_t b, uint32_t ph) {
  if (mbar_try(b, ph)) return;
#pragma unroll 1
  for (int i = 0; i < (1 << 16); i++)
    if (mbar_try_long(b, ph)) return;
  __trap();
}
DEVI uint32_t lane_id() { uint32_t l; asm volatile("mov.u32 %0, %%laneid;" : "=r"(l)); return l; }
DEVI int cta_id() { int b; asm volatile("mov.u32 %0, %%ctaid.x;" : "=r"(b)); return b; }
DEVI bool elect_one() {
  uint32_t r;
  asm volatile("{\n.reg .pred p;\nelect.sync _|p, 0xffffffff;\nselp.u32 %0, 1, 0, p;\n}" : "=r"(r));
  return r;
}
DEVI void fence_mbar_init() { asm volatile("fence.mbarrier_init.release.cluster;" ::: "memory"); }
DEVI void fence_async_smem() { asm volatile("fence.proxy.async.shared::cta;" ::: "memory"); }
DEVI void fence_async_gmem() { asm volatile("fence.proxy.async.global;" ::: "memory"); }
DEVI void tma_store4(const CUtensorMap* m, uint32_t src, int x, int y, int z, int w) {
  asm volatile("cp.async.bulk.tensor.4d.global.shared::cta.bulk_group [%0, {%2, %3, %4, %5}], [%1];" ::"l"(m), "r"(src), "r"(x), "r"(y), "r"(z), "r"(w) : "memory");
}
DEVI void sts128(uint32_t a, uint32_t x, uint32_t y, uint32_t z, uint32_t w) { asm volatile("st.shared.v4.u32 [%0], {%1, %2, %3, %4};" ::"r"(a), "r"(x), "r"(y), "r"(z), "r"(w) : "memory"); }
DEVI void sts32(uint32_t a, uint32_t v) { asm volatile("st.shared.u32 [%0], %1;" ::"r"(a), "r"(v) : "memory"); }
DEVI uint32_t lds32(uint32_t a) { uint32_t v; asm volatile("ld.volatile.shared.u32 %0, [%1];" : "=r"(v) : "r"(a) : "memory"); return v; }
DEVI uint2 lds64(uint32_t a) { uint2 v; asm volatile("ld.volatile.shared.v2.u32 {%0, %1}, [%2];" : "=r"(v.x), "=r"(v.y) : "r"(a) : "memory"); return v; }
DEVI uint4 lds128(uint32_t a) { uint4 v; asm volatile("ld.volatile.shared.v4.u32 {%0, %1, %2, %3}, [%4];" : "=r"(v.x), "=r"(v.y), "=r"(v.z), "=r"(v.w) : "r"(a) : "memory"); return v; }
DEVI uint32_t max4(uint4 v) { return max(max(v.x, v.y), max(v.z, v.w)); }
DEVI uint32_t any_empty(int id, int n, uint32_t m) {
  uint32_t r;
  asm volatile("{\n.reg .pred p, q;\nsetp.eq.u32 p, %3, 0xFFFFFFFF;\nbar.red.or.pred q, %1, %2, p;\nselp.u32 %0, 1, 0, q;\n}" : "=r"(r) : "r"(id), "r"(n), "r"(m) : "memory");
  return r;
}
DEVI void bar_sync(int id, int n) { asm volatile("bar.sync %0, %1;" ::"r"(id), "r"(n) : "memory"); }
DEVI void bar_arrive(int id, int n) { asm volatile("bar.arrive %0, %1;" ::"r"(id), "r"(n) : "memory"); }
template <int N> DEVI void reg_inc() { asm volatile("setmaxnreg.inc.sync.aligned.u32 %0;" ::"n"(N)); }
template <int N> DEVI void reg_dec() { asm volatile("setmaxnreg.dec.sync.aligned.u32 %0;" ::"n"(N)); }
DEVI void tma2(uint32_t dst, const CUtensorMap* m, int x, int y, uint32_t bar) {
  asm volatile("cp.async.bulk.tensor.2d.shared::cluster.global.mbarrier::complete_tx::bytes [%0], [%1, {%3, %4}], [%2];"
               ::"r"(dst), "l"(m), "r"(bar), "r"(x), "r"(y) : "memory");
}
DEVI void tma3(uint32_t dst, const CUtensorMap* m, int x, int y, int z, uint32_t bar) {
  asm volatile("cp.async.bulk.tensor.3d.shared::cluster.global.mbarrier::complete_tx::bytes [%0], [%1, {%3, %4, %5}], [%2];"
               ::"r"(dst), "l"(m), "r"(bar), "r"(x), "r"(y), "r"(z) : "memory");
}
DEVI void tma4(uint32_t dst, const CUtensorMap* m, int x, int y, int z, int w, uint32_t bar) {
  asm volatile("cp.async.bulk.tensor.4d.shared::cluster.global.mbarrier::complete_tx::bytes [%0], [%1, {%3, %4, %5, %6}], [%2];"
               ::"r"(dst), "l"(m), "r"(bar), "r"(x), "r"(y), "r"(z), "r"(w) : "memory");
}
DEVI void tma5(uint32_t dst, const CUtensorMap* m, int x, int y, int z, int w, int v, uint32_t bar) {
  asm volatile("cp.async.bulk.tensor.5d.shared::cluster.global.mbarrier::complete_tx::bytes [%0], [%1, {%3, %4, %5, %6, %7}], [%2];"
               ::"r"(dst), "l"(m), "r"(bar), "r"(x), "r"(y), "r"(z), "r"(w), "r"(v) : "memory");
}
DEVI void bulk_load(uint32_t dst, const void* src, uint32_t bytes, uint32_t bar) {
  asm volatile("cp.async.bulk.shared::cluster.global.mbarrier::complete_tx::bytes [%0], [%1], %2, [%3];"
               ::"r"(dst), "l"(src), "r"(bytes), "r"(bar) : "memory");
}
DEVI void l2_prefetch(const void* src, uint32_t bytes) { asm volatile("cp.async.bulk.prefetch.L2.global [%0], %1;" ::"l"(src), "r"(bytes) : "memory"); }
DEVI void wg_fence() { asm volatile("wgmma.fence.sync.aligned;" ::: "memory"); }
DEVI void wg_commit() { asm volatile("wgmma.commit_group.sync.aligned;" ::: "memory"); }
template <int N> DEVI void wg_wait() { asm volatile("wgmma.wait_group.sync.aligned %0;" ::"n"(N) : "memory"); }
__host__ DEVI uint64_t mkdesc(uint32_t addr, uint32_t lbo, uint32_t sbo, uint32_t swz) {
  return (uint64_t)((addr & 0x3FFFF) >> 4) | ((uint64_t)(lbo >> 4) << 16) | ((uint64_t)(sbo >> 4) << 32) | ((uint64_t)swz << 62);
}
DEVI unsigned ld_acquire(const unsigned* p) { unsigned v; asm volatile("ld.acquire.gpu.global.u32 %0, [%1];" : "=r"(v) : "l"(p) : "memory"); return v; }
DEVI uint2 ldg64(const void* p) { uint2 v; asm volatile("ld.global.v2.u32 {%0, %1}, [%2];" : "=r"(v.x), "=r"(v.y) : "l"(p) : "memory"); return v; }
DEVI void red_release(unsigned* p, unsigned v) { asm volatile("red.release.gpu.global.add.u32 [%0], %1;" ::"l"(p), "r"(v) : "memory"); }
DEVI void red_relaxed(unsigned* p, unsigned v) { asm volatile("red.relaxed.gpu.global.add.u32 [%0], %1;" ::"l"(p), "r"(v) : "memory"); }
DEVI void st_relaxed(void* p, uint32_t v) { asm volatile("st.relaxed.gpu.global.u32 [%0], %1;" ::"l"(p), "r"(v) : "memory"); }
DEVI void st_relaxed2(void* p, uint32_t a, uint32_t b) { asm volatile("st.relaxed.gpu.global.v2.u32 [%0], {%1, %2};" ::"l"(p), "r"(a), "r"(b) : "memory"); }
DEVI void wait_count(const unsigned* p, unsigned target) {
#pragma unroll 1
  for (int i = 0; i < (1 << 23); i++) {
    if (ld_acquire(p) >= target) return;
    __nanosleep(40);
  }
  __trap();
}
DEVI uint32_t pack_h2(float lo, float hi) { uint32_t r; asm("cvt.rn.f16x2.f32 %0, %1, %2;" : "=r"(r) : "f"(hi), "f"(lo)); return r; }
DEVI uint32_t pack_b2(float lo, float hi) { uint32_t r; asm("cvt.rn.bf16x2.f32 %0, %1, %2;" : "=r"(r) : "f"(hi), "f"(lo)); return r; }
DEVI float rcp_approx(float x) { float y; asm("rcp.approx.ftz.f32 %0, %1;" : "=f"(y) : "f"(x)); return y; }
DEVI float ex2_approx(float x) { float y; asm("ex2.approx.ftz.f32 %0, %1;" : "=f"(y) : "f"(x)); return y; }
DEVI float sqrt_approx(float x) { float y; asm("sqrt.approx.ftz.f32 %0, %1;" : "=f"(y) : "f"(x)); return y; }
DEVI uint32_t habs_max(uint32_t a, uint32_t b) { uint32_t r; asm("max.NaN.xorsign.abs.bf16x2 %0, %1, %2;" : "=r"(r) : "r"(a), "r"(b)); return r; }
DEVI uint32_t mul_b2(uint32_t a, uint32_t b) { uint32_t r; asm("mul.rn.bf16x2 %0, %1, %2;" : "=r"(r) : "r"(a), "r"(b)); return r; }
DEVI float bf_lo(uint32_t v) { return __uint_as_float(v << 16); }
DEVI float bf_hi(uint32_t v) { return __uint_as_float(v & 0xFFFF0000u); }
DEVI float h_lo(uint32_t v) { return __low2float(*(__half2*)&v); }
DEVI float h_hi(uint32_t v) { return __high2float(*(__half2*)&v); }
DEVI float bf_round(float v) { return __bfloat162float(__float2bfloat16_rn(v)); }

__device__ __forceinline__ void rs_n8(float* d, const uint32_t* a, uint64_t db, int add = 1) {
  asm volatile("{\n.reg .pred p;\nsetp.ne.b32 p, %9, 0;\nwgmma.mma_async.sync.aligned.m64n8k16.f32.bf16.bf16 {"
      "%0, %1, %2, %3"
      "}, {%4, %5, %6, %7}, %8, p, 1, 1, 1;\n}\n"
      :
      "+f"(d[0]), "+f"(d[1]), "+f"(d[2]), "+f"(d[3])
      : "r"(a[0]), "r"(a[1]), "r"(a[2]), "r"(a[3]), "l"(db), "r"(add));
}
__device__ __forceinline__ void rs_n16(float* d, const uint32_t* a, uint64_t db, int add = 1) {
  asm volatile("{\n.reg .pred p;\nsetp.ne.b32 p, %13, 0;\nwgmma.mma_async.sync.aligned.m64n16k16.f32.bf16.bf16 {"
      "%0, %1, %2, %3, %4, %5, %6, %7"
      "}, {%8, %9, %10, %11}, %12, p, 1, 1, 1;\n}\n"
      :
      "+f"(d[0]), "+f"(d[1]), "+f"(d[2]), "+f"(d[3]), "+f"(d[4]), "+f"(d[5]), "+f"(d[6]), "+f"(d[7])
      : "r"(a[0]), "r"(a[1]), "r"(a[2]), "r"(a[3]), "l"(db), "r"(add));
}
__device__ __forceinline__ void rs_n24(float* d, const uint32_t* a, uint64_t db, int add = 1) {
  asm volatile("{\n.reg .pred p;\nsetp.ne.b32 p, %17, 0;\nwgmma.mma_async.sync.aligned.m64n24k16.f32.bf16.bf16 {"
      "%0, %1, %2, %3, %4, %5, %6, %7, %8, %9, %10, %11"
      "}, {%12, %13, %14, %15}, %16, p, 1, 1, 1;\n}\n"
      :
      "+f"(d[0]), "+f"(d[1]), "+f"(d[2]), "+f"(d[3]), "+f"(d[4]), "+f"(d[5]), "+f"(d[6]), "+f"(d[7]), "+f"(d[8]), "+f"(d[9]), "+f"(d[10]), "+f"(d[11])
      : "r"(a[0]), "r"(a[1]), "r"(a[2]), "r"(a[3]), "l"(db), "r"(add));
}
__device__ __forceinline__ void rs_n32(float* d, const uint32_t* a, uint64_t db, int add = 1) {
  asm volatile("{\n.reg .pred p;\nsetp.ne.b32 p, %21, 0;\nwgmma.mma_async.sync.aligned.m64n32k16.f32.bf16.bf16 {"
      "%0, %1, %2, %3, %4, %5, %6, %7, %8, %9, %10, %11, %12, %13, %14, %15"
      "}, {%16, %17, %18, %19}, %20, p, 1, 1, 1;\n}\n"
      :
      "+f"(d[0]), "+f"(d[1]), "+f"(d[2]), "+f"(d[3]), "+f"(d[4]), "+f"(d[5]), "+f"(d[6]), "+f"(d[7]), "+f"(d[8]), "+f"(d[9]), "+f"(d[10]), "+f"(d[11]),
      "+f"(d[12]), "+f"(d[13]), "+f"(d[14]), "+f"(d[15])
      : "r"(a[0]), "r"(a[1]), "r"(a[2]), "r"(a[3]), "l"(db), "r"(add));
}
__device__ __forceinline__ void rs_n40(float* d, const uint32_t* a, uint64_t db, int add = 1) {
  asm volatile("{\n.reg .pred p;\nsetp.ne.b32 p, %25, 0;\nwgmma.mma_async.sync.aligned.m64n40k16.f32.bf16.bf16 {"
      "%0, %1, %2, %3, %4, %5, %6, %7, %8, %9, %10, %11, %12, %13, %14, %15, %16, %17, %18, %19"
      "}, {%20, %21, %22, %23}, %24, p, 1, 1, 1;\n}\n"
      :
      "+f"(d[0]), "+f"(d[1]), "+f"(d[2]), "+f"(d[3]), "+f"(d[4]), "+f"(d[5]), "+f"(d[6]), "+f"(d[7]), "+f"(d[8]), "+f"(d[9]), "+f"(d[10]), "+f"(d[11]),
      "+f"(d[12]), "+f"(d[13]), "+f"(d[14]), "+f"(d[15]), "+f"(d[16]), "+f"(d[17]), "+f"(d[18]), "+f"(d[19])
      : "r"(a[0]), "r"(a[1]), "r"(a[2]), "r"(a[3]), "l"(db), "r"(add));
}
__device__ __forceinline__ void rs_n48(float* d, const uint32_t* a, uint64_t db, int add = 1) {
  asm volatile("{\n.reg .pred p;\nsetp.ne.b32 p, %29, 0;\nwgmma.mma_async.sync.aligned.m64n48k16.f32.bf16.bf16 {"
      "%0, %1, %2, %3, %4, %5, %6, %7, %8, %9, %10, %11, %12, %13, %14, %15, %16, %17, %18, %19, %20, %21, %22, %23"
      "}, {%24, %25, %26, %27}, %28, p, 1, 1, 1;\n}\n"
      :
      "+f"(d[0]), "+f"(d[1]), "+f"(d[2]), "+f"(d[3]), "+f"(d[4]), "+f"(d[5]), "+f"(d[6]), "+f"(d[7]), "+f"(d[8]), "+f"(d[9]), "+f"(d[10]), "+f"(d[11]),
      "+f"(d[12]), "+f"(d[13]), "+f"(d[14]), "+f"(d[15]), "+f"(d[16]), "+f"(d[17]), "+f"(d[18]), "+f"(d[19]), "+f"(d[20]), "+f"(d[21]), "+f"(d[22]), "+f"(d[23])
      : "r"(a[0]), "r"(a[1]), "r"(a[2]), "r"(a[3]), "l"(db), "r"(add));
}
__device__ __forceinline__ void rs_n56(float* d, const uint32_t* a, uint64_t db, int add = 1) {
  asm volatile("{\n.reg .pred p;\nsetp.ne.b32 p, %33, 0;\nwgmma.mma_async.sync.aligned.m64n56k16.f32.bf16.bf16 {"
      "%0, %1, %2, %3, %4, %5, %6, %7, %8, %9, %10, %11, %12, %13, %14, %15, %16, %17, %18, %19, %20, %21, %22, %23, "
      "%24, %25, %26, %27"
      "}, {%28, %29, %30, %31}, %32, p, 1, 1, 1;\n}\n"
      :
      "+f"(d[0]), "+f"(d[1]), "+f"(d[2]), "+f"(d[3]), "+f"(d[4]), "+f"(d[5]), "+f"(d[6]), "+f"(d[7]), "+f"(d[8]), "+f"(d[9]), "+f"(d[10]), "+f"(d[11]),
      "+f"(d[12]), "+f"(d[13]), "+f"(d[14]), "+f"(d[15]), "+f"(d[16]), "+f"(d[17]), "+f"(d[18]), "+f"(d[19]), "+f"(d[20]), "+f"(d[21]), "+f"(d[22]), "+f"(d[23]),
      "+f"(d[24]), "+f"(d[25]), "+f"(d[26]), "+f"(d[27])
      : "r"(a[0]), "r"(a[1]), "r"(a[2]), "r"(a[3]), "l"(db), "r"(add));
}
__device__ __forceinline__ void rs_n64(float* d, const uint32_t* a, uint64_t db, int add = 1) {
  asm volatile("{\n.reg .pred p;\nsetp.ne.b32 p, %37, 0;\nwgmma.mma_async.sync.aligned.m64n64k16.f32.bf16.bf16 {"
      "%0, %1, %2, %3, %4, %5, %6, %7, %8, %9, %10, %11, %12, %13, %14, %15, %16, %17, %18, %19, %20, %21, %22, %23, "
      "%24, %25, %26, %27, %28, %29, %30, %31"
      "}, {%32, %33, %34, %35}, %36, p, 1, 1, 1;\n}\n"
      :
      "+f"(d[0]), "+f"(d[1]), "+f"(d[2]), "+f"(d[3]), "+f"(d[4]), "+f"(d[5]), "+f"(d[6]), "+f"(d[7]), "+f"(d[8]), "+f"(d[9]), "+f"(d[10]), "+f"(d[11]),
      "+f"(d[12]), "+f"(d[13]), "+f"(d[14]), "+f"(d[15]), "+f"(d[16]), "+f"(d[17]), "+f"(d[18]), "+f"(d[19]), "+f"(d[20]), "+f"(d[21]), "+f"(d[22]), "+f"(d[23]),
      "+f"(d[24]), "+f"(d[25]), "+f"(d[26]), "+f"(d[27]), "+f"(d[28]), "+f"(d[29]), "+f"(d[30]), "+f"(d[31])
      : "r"(a[0]), "r"(a[1]), "r"(a[2]), "r"(a[3]), "l"(db), "r"(add));
}
__device__ __forceinline__ void rs_n72(float* d, const uint32_t* a, uint64_t db, int add = 1) {
  asm volatile("{\n.reg .pred p;\nsetp.ne.b32 p, %41, 0;\nwgmma.mma_async.sync.aligned.m64n72k16.f32.bf16.bf16 {"
      "%0, %1, %2, %3, %4, %5, %6, %7, %8, %9, %10, %11, %12, %13, %14, %15, %16, %17, %18, %19, %20, %21, %22, %23, "
      "%24, %25, %26, %27, %28, %29, %30, %31, %32, %33, %34, %35"
      "}, {%36, %37, %38, %39}, %40, p, 1, 1, 1;\n}\n"
      :
      "+f"(d[0]), "+f"(d[1]), "+f"(d[2]), "+f"(d[3]), "+f"(d[4]), "+f"(d[5]), "+f"(d[6]), "+f"(d[7]), "+f"(d[8]), "+f"(d[9]), "+f"(d[10]), "+f"(d[11]),
      "+f"(d[12]), "+f"(d[13]), "+f"(d[14]), "+f"(d[15]), "+f"(d[16]), "+f"(d[17]), "+f"(d[18]), "+f"(d[19]), "+f"(d[20]), "+f"(d[21]), "+f"(d[22]), "+f"(d[23]),
      "+f"(d[24]), "+f"(d[25]), "+f"(d[26]), "+f"(d[27]), "+f"(d[28]), "+f"(d[29]), "+f"(d[30]), "+f"(d[31]), "+f"(d[32]), "+f"(d[33]), "+f"(d[34]), "+f"(d[35])
      : "r"(a[0]), "r"(a[1]), "r"(a[2]), "r"(a[3]), "l"(db), "r"(add));
}
__device__ __forceinline__ void rs_n80(float* d, const uint32_t* a, uint64_t db, int add = 1) {
  asm volatile("{\n.reg .pred p;\nsetp.ne.b32 p, %45, 0;\nwgmma.mma_async.sync.aligned.m64n80k16.f32.bf16.bf16 {"
      "%0, %1, %2, %3, %4, %5, %6, %7, %8, %9, %10, %11, %12, %13, %14, %15, %16, %17, %18, %19, %20, %21, %22, %23, "
      "%24, %25, %26, %27, %28, %29, %30, %31, %32, %33, %34, %35, %36, %37, %38, %39"
      "}, {%40, %41, %42, %43}, %44, p, 1, 1, 1;\n}\n"
      :
      "+f"(d[0]), "+f"(d[1]), "+f"(d[2]), "+f"(d[3]), "+f"(d[4]), "+f"(d[5]), "+f"(d[6]), "+f"(d[7]), "+f"(d[8]), "+f"(d[9]), "+f"(d[10]), "+f"(d[11]),
      "+f"(d[12]), "+f"(d[13]), "+f"(d[14]), "+f"(d[15]), "+f"(d[16]), "+f"(d[17]), "+f"(d[18]), "+f"(d[19]), "+f"(d[20]), "+f"(d[21]), "+f"(d[22]), "+f"(d[23]),
      "+f"(d[24]), "+f"(d[25]), "+f"(d[26]), "+f"(d[27]), "+f"(d[28]), "+f"(d[29]), "+f"(d[30]), "+f"(d[31]), "+f"(d[32]), "+f"(d[33]), "+f"(d[34]), "+f"(d[35]),
      "+f"(d[36]), "+f"(d[37]), "+f"(d[38]), "+f"(d[39])
      : "r"(a[0]), "r"(a[1]), "r"(a[2]), "r"(a[3]), "l"(db), "r"(add));
}
__device__ __forceinline__ void rs_n88(float* d, const uint32_t* a, uint64_t db, int add = 1) {
  asm volatile("{\n.reg .pred p;\nsetp.ne.b32 p, %49, 0;\nwgmma.mma_async.sync.aligned.m64n88k16.f32.bf16.bf16 {"
      "%0, %1, %2, %3, %4, %5, %6, %7, %8, %9, %10, %11, %12, %13, %14, %15, %16, %17, %18, %19, %20, %21, %22, %23, "
      "%24, %25, %26, %27, %28, %29, %30, %31, %32, %33, %34, %35, %36, %37, %38, %39, %40, %41, %42, %43"
      "}, {%44, %45, %46, %47}, %48, p, 1, 1, 1;\n}\n"
      :
      "+f"(d[0]), "+f"(d[1]), "+f"(d[2]), "+f"(d[3]), "+f"(d[4]), "+f"(d[5]), "+f"(d[6]), "+f"(d[7]), "+f"(d[8]), "+f"(d[9]), "+f"(d[10]), "+f"(d[11]),
      "+f"(d[12]), "+f"(d[13]), "+f"(d[14]), "+f"(d[15]), "+f"(d[16]), "+f"(d[17]), "+f"(d[18]), "+f"(d[19]), "+f"(d[20]), "+f"(d[21]), "+f"(d[22]), "+f"(d[23]),
      "+f"(d[24]), "+f"(d[25]), "+f"(d[26]), "+f"(d[27]), "+f"(d[28]), "+f"(d[29]), "+f"(d[30]), "+f"(d[31]), "+f"(d[32]), "+f"(d[33]), "+f"(d[34]), "+f"(d[35]),
      "+f"(d[36]), "+f"(d[37]), "+f"(d[38]), "+f"(d[39]), "+f"(d[40]), "+f"(d[41]), "+f"(d[42]), "+f"(d[43])
      : "r"(a[0]), "r"(a[1]), "r"(a[2]), "r"(a[3]), "l"(db), "r"(add));
}
__device__ __forceinline__ void rs_n96(float* d, const uint32_t* a, uint64_t db, int add = 1) {
  asm volatile("{\n.reg .pred p;\nsetp.ne.b32 p, %53, 0;\nwgmma.mma_async.sync.aligned.m64n96k16.f32.bf16.bf16 {"
      "%0, %1, %2, %3, %4, %5, %6, %7, %8, %9, %10, %11, %12, %13, %14, %15, %16, %17, %18, %19, %20, %21, %22, %23, "
      "%24, %25, %26, %27, %28, %29, %30, %31, %32, %33, %34, %35, %36, %37, %38, %39, %40, %41, %42, %43, %44, %45, %46, %47"
      "}, {%48, %49, %50, %51}, %52, p, 1, 1, 1;\n}\n"
      :
      "+f"(d[0]), "+f"(d[1]), "+f"(d[2]), "+f"(d[3]), "+f"(d[4]), "+f"(d[5]), "+f"(d[6]), "+f"(d[7]), "+f"(d[8]), "+f"(d[9]), "+f"(d[10]), "+f"(d[11]),
      "+f"(d[12]), "+f"(d[13]), "+f"(d[14]), "+f"(d[15]), "+f"(d[16]), "+f"(d[17]), "+f"(d[18]), "+f"(d[19]), "+f"(d[20]), "+f"(d[21]), "+f"(d[22]), "+f"(d[23]),
      "+f"(d[24]), "+f"(d[25]), "+f"(d[26]), "+f"(d[27]), "+f"(d[28]), "+f"(d[29]), "+f"(d[30]), "+f"(d[31]), "+f"(d[32]), "+f"(d[33]), "+f"(d[34]), "+f"(d[35]),
      "+f"(d[36]), "+f"(d[37]), "+f"(d[38]), "+f"(d[39]), "+f"(d[40]), "+f"(d[41]), "+f"(d[42]), "+f"(d[43]), "+f"(d[44]), "+f"(d[45]), "+f"(d[46]), "+f"(d[47])
      : "r"(a[0]), "r"(a[1]), "r"(a[2]), "r"(a[3]), "l"(db), "r"(add));
}
__device__ __forceinline__ void mma_n64(float* d, uint64_t da, uint64_t db, int add = 1) {
  asm volatile("{\n.reg .pred p;\nsetp.ne.b32 p, %34, 0;\nwgmma.mma_async.sync.aligned.m64n64k16.f32.bf16.bf16 {"
      "%0, %1, %2, %3, %4, %5, %6, %7, %8, %9, %10, %11, %12, %13, %14, %15, %16, %17, %18, %19, %20, %21, %22, %23, "
      "%24, %25, %26, %27, %28, %29, %30, %31"
      "}, %32, %33, p, 1, 1, 0, 0;\n}\n"
      :
      "+f"(d[0]), "+f"(d[1]), "+f"(d[2]), "+f"(d[3]), "+f"(d[4]), "+f"(d[5]), "+f"(d[6]), "+f"(d[7]), "+f"(d[8]), "+f"(d[9]), "+f"(d[10]), "+f"(d[11]),
      "+f"(d[12]), "+f"(d[13]), "+f"(d[14]), "+f"(d[15]), "+f"(d[16]), "+f"(d[17]), "+f"(d[18]), "+f"(d[19]), "+f"(d[20]), "+f"(d[21]), "+f"(d[22]), "+f"(d[23]),
      "+f"(d[24]), "+f"(d[25]), "+f"(d[26]), "+f"(d[27]), "+f"(d[28]), "+f"(d[29]), "+f"(d[30]), "+f"(d[31])
      : "l"(da), "l"(db), "r"(add));
}
__device__ __forceinline__ void mma_n64_z(float* d, uint64_t da, uint64_t db) {
  asm volatile("{\n.reg .pred p;\nsetp.ne.b32 p, 0, 0;\nwgmma.mma_async.sync.aligned.m64n64k16.f32.bf16.bf16 {"
      "%0, %1, %2, %3, %4, %5, %6, %7, %8, %9, %10, %11, %12, %13, %14, %15, %16, %17, %18, %19, %20, %21, %22, %23, "
      "%24, %25, %26, %27, %28, %29, %30, %31"
      "}, %32, %33, p, 1, 1, 0, 0;\n}\n"
      :
      "=f"(d[0]), "=f"(d[1]), "=f"(d[2]), "=f"(d[3]), "=f"(d[4]), "=f"(d[5]), "=f"(d[6]), "=f"(d[7]), "=f"(d[8]), "=f"(d[9]), "=f"(d[10]), "=f"(d[11]),
      "=f"(d[12]), "=f"(d[13]), "=f"(d[14]), "=f"(d[15]), "=f"(d[16]), "=f"(d[17]), "=f"(d[18]), "=f"(d[19]), "=f"(d[20]), "=f"(d[21]), "=f"(d[22]), "=f"(d[23]),
      "=f"(d[24]), "=f"(d[25]), "=f"(d[26]), "=f"(d[27]), "=f"(d[28]), "=f"(d[29]), "=f"(d[30]), "=f"(d[31])
      : "l"(da), "l"(db));
}
__device__ __forceinline__ void mma_n64_ta(float* d, uint64_t da, uint64_t db, int add = 1) {
  asm volatile("{\n.reg .pred p;\nsetp.ne.b32 p, %34, 0;\nwgmma.mma_async.sync.aligned.m64n64k16.f32.bf16.bf16 {"
      "%0, %1, %2, %3, %4, %5, %6, %7, %8, %9, %10, %11, %12, %13, %14, %15, %16, %17, %18, %19, %20, %21, %22, %23, "
      "%24, %25, %26, %27, %28, %29, %30, %31"
      "}, %32, %33, p, 1, 1, 1, 0;\n}\n"
      :
      "+f"(d[0]), "+f"(d[1]), "+f"(d[2]), "+f"(d[3]), "+f"(d[4]), "+f"(d[5]), "+f"(d[6]), "+f"(d[7]), "+f"(d[8]), "+f"(d[9]), "+f"(d[10]), "+f"(d[11]),
      "+f"(d[12]), "+f"(d[13]), "+f"(d[14]), "+f"(d[15]), "+f"(d[16]), "+f"(d[17]), "+f"(d[18]), "+f"(d[19]), "+f"(d[20]), "+f"(d[21]), "+f"(d[22]), "+f"(d[23]),
      "+f"(d[24]), "+f"(d[25]), "+f"(d[26]), "+f"(d[27]), "+f"(d[28]), "+f"(d[29]), "+f"(d[30]), "+f"(d[31])
      : "l"(da), "l"(db), "r"(add));
}
__device__ __forceinline__ void mma_n80_ta(float* d, uint64_t da, uint64_t db, int add = 1) {
  asm volatile("{\n.reg .pred p;\nsetp.ne.b32 p, %42, 0;\nwgmma.mma_async.sync.aligned.m64n80k16.f32.bf16.bf16 {"
      "%0, %1, %2, %3, %4, %5, %6, %7, %8, %9, %10, %11, %12, %13, %14, %15, %16, %17, %18, %19, %20, %21, %22, %23, "
      "%24, %25, %26, %27, %28, %29, %30, %31, %32, %33, %34, %35, %36, %37, %38, %39"
      "}, %40, %41, p, 1, 1, 1, 0;\n}\n"
      :
      "+f"(d[0]), "+f"(d[1]), "+f"(d[2]), "+f"(d[3]), "+f"(d[4]), "+f"(d[5]), "+f"(d[6]), "+f"(d[7]), "+f"(d[8]), "+f"(d[9]), "+f"(d[10]), "+f"(d[11]),
      "+f"(d[12]), "+f"(d[13]), "+f"(d[14]), "+f"(d[15]), "+f"(d[16]), "+f"(d[17]), "+f"(d[18]), "+f"(d[19]), "+f"(d[20]), "+f"(d[21]), "+f"(d[22]), "+f"(d[23]),
      "+f"(d[24]), "+f"(d[25]), "+f"(d[26]), "+f"(d[27]), "+f"(d[28]), "+f"(d[29]), "+f"(d[30]), "+f"(d[31]), "+f"(d[32]), "+f"(d[33]), "+f"(d[34]), "+f"(d[35]),
      "+f"(d[36]), "+f"(d[37]), "+f"(d[38]), "+f"(d[39])
      : "l"(da), "l"(db), "r"(add));
}
__device__ __forceinline__ void mma_n80_ta_tb(float* d, uint64_t da, uint64_t db, int add = 1) {
  asm volatile("{\n.reg .pred p;\nsetp.ne.b32 p, %42, 0;\nwgmma.mma_async.sync.aligned.m64n80k16.f32.bf16.bf16 {"
      "%0, %1, %2, %3, %4, %5, %6, %7, %8, %9, %10, %11, %12, %13, %14, %15, %16, %17, %18, %19, %20, %21, %22, %23, "
      "%24, %25, %26, %27, %28, %29, %30, %31, %32, %33, %34, %35, %36, %37, %38, %39"
      "}, %40, %41, p, 1, 1, 1, 1;\n}\n"
      :
      "+f"(d[0]), "+f"(d[1]), "+f"(d[2]), "+f"(d[3]), "+f"(d[4]), "+f"(d[5]), "+f"(d[6]), "+f"(d[7]), "+f"(d[8]), "+f"(d[9]), "+f"(d[10]), "+f"(d[11]),
      "+f"(d[12]), "+f"(d[13]), "+f"(d[14]), "+f"(d[15]), "+f"(d[16]), "+f"(d[17]), "+f"(d[18]), "+f"(d[19]), "+f"(d[20]), "+f"(d[21]), "+f"(d[22]), "+f"(d[23]),
      "+f"(d[24]), "+f"(d[25]), "+f"(d[26]), "+f"(d[27]), "+f"(d[28]), "+f"(d[29]), "+f"(d[30]), "+f"(d[31]), "+f"(d[32]), "+f"(d[33]), "+f"(d[34]), "+f"(d[35]),
      "+f"(d[36]), "+f"(d[37]), "+f"(d[38]), "+f"(d[39])
      : "l"(da), "l"(db), "r"(add));
}
__device__ __forceinline__ void qk_n128_z(uint32_t (&d)[32], uint32_t a0, uint32_t a1, uint32_t a2, uint32_t a3, uint64_t db) {
  asm volatile("{\n.reg .pred p;\nsetp.ne.b32 p, 0, 0;\nwgmma.mma_async.sync.aligned.m64n128k16.f16.f16.f16 {"
      "%0, %1, %2, %3, %4, %5, %6, %7, %8, %9, %10, %11, %12, %13, %14, %15, %16, %17, %18, %19, %20, %21, %22, %23, "
      "%24, %25, %26, %27, %28, %29, %30, %31"
      "}, {%32, %33, %34, %35}, %36, p, 1, 1, 0;\n}\n"
      :
      "=r"(d[0]), "=r"(d[1]), "=r"(d[2]), "=r"(d[3]), "=r"(d[4]), "=r"(d[5]), "=r"(d[6]), "=r"(d[7]), "=r"(d[8]), "=r"(d[9]), "=r"(d[10]), "=r"(d[11]),
      "=r"(d[12]), "=r"(d[13]), "=r"(d[14]), "=r"(d[15]), "=r"(d[16]), "=r"(d[17]), "=r"(d[18]), "=r"(d[19]), "=r"(d[20]), "=r"(d[21]), "=r"(d[22]), "=r"(d[23]),
      "=r"(d[24]), "=r"(d[25]), "=r"(d[26]), "=r"(d[27]), "=r"(d[28]), "=r"(d[29]), "=r"(d[30]), "=r"(d[31])
      : "r"(a0), "r"(a1), "r"(a2), "r"(a3), "l"(db));
}
__device__ __forceinline__ void qk_n128_ss(uint32_t (&d)[32], uint64_t da, uint64_t db) {
  asm volatile("{\n.reg .pred p;\nsetp.ne.b32 p, 1, 0;\nwgmma.mma_async.sync.aligned.m64n128k16.f16.f16.f16 {"
      "%0, %1, %2, %3, %4, %5, %6, %7, %8, %9, %10, %11, %12, %13, %14, %15, %16, %17, %18, %19, %20, %21, %22, %23, "
      "%24, %25, %26, %27, %28, %29, %30, %31"
      "}, %32, %33, p, 1, 1, 0, 0;\n}\n"
      :
      "+r"(d[0]), "+r"(d[1]), "+r"(d[2]), "+r"(d[3]), "+r"(d[4]), "+r"(d[5]), "+r"(d[6]), "+r"(d[7]), "+r"(d[8]), "+r"(d[9]), "+r"(d[10]), "+r"(d[11]),
      "+r"(d[12]), "+r"(d[13]), "+r"(d[14]), "+r"(d[15]), "+r"(d[16]), "+r"(d[17]), "+r"(d[18]), "+r"(d[19]), "+r"(d[20]), "+r"(d[21]), "+r"(d[22]), "+r"(d[23]),
      "+r"(d[24]), "+r"(d[25]), "+r"(d[26]), "+r"(d[27]), "+r"(d[28]), "+r"(d[29]), "+r"(d[30]), "+r"(d[31])
      : "l"(da), "l"(db));
}
__device__ __forceinline__ void pv_n24(uint32_t (&d)[6], uint32_t a0, uint32_t a1, uint32_t a2, uint32_t a3, uint64_t db) {
  asm volatile("{\n.reg .pred p;\nsetp.ne.b32 p, 1, 0;\nwgmma.mma_async.sync.aligned.m64n24k16.f16.f16.f16 {"
      "%0, %1, %2, %3, %4, %5"
      "}, {%6, %7, %8, %9}, %10, p, 1, 1, 1;\n}\n"
      :
      "+r"(d[0]), "+r"(d[1]), "+r"(d[2]), "+r"(d[3]), "+r"(d[4]), "+r"(d[5])
      : "r"(a0), "r"(a1), "r"(a2), "r"(a3), "l"(db));
}


constexpr uint32_t SB = 1024;
constexpr int NS = 5, S_STAGE = 24576, W_O1 = 9 * 8192, A_BASE = W_O1 + 6 * 10240, A_SLOT = 20480, A_Q2 = A_BASE + 4 * A_SLOT;
constexpr int A_QT = A_Q2 + 10240, M_BARS = A_QT + 4096, M_SMEM = M_BARS + 1024;
constexpr int B_KVFULL = 0, B_O2T = 32, B_KVEMPTY = 128, B_DONE = 160, B_QOK = 168, B_EMPTY = 192, B_H = B_EMPTY + 8 * NS;
constexpr int B_FREE = 256, B_FULL = 264, B_WO = B_FULL + 8 * NS, B_O1 = B_WO + 8, B_O2 = B_O1 + 72, B_Q2 = B_O2 + 64;
constexpr int B_GATE = B_O2 + 72, B_PUB = B_GATE + 8, B_SEEN = B_PUB + 8, B_O1E = 480, B_SPARE = 104;
constexpr int W_MASK = 512, W_QUEUE = W_MASK + 8, W_CONST = 576;
constexpr int B_QFULL = 640, B_QEMPTY = 672, B_REL = 704, B_GO = 720, B_RING = 728, W_KMAX = 568;
static_assert(B_SEEN + 8 <= B_O1E && B_H < B_FREE, "");
__host__ DEVI uint32_t o_block(int b) { return SB + (b < 6 ? W_O1 + b * 10240 : (b < 8 ? A_BASE + (b - 6) * 10240 : A_Q2)); }

constexpr int QST = 4, Q_A = 16384, Q_B = 40960, Q_STAGE = Q_A + Q_B;
static_assert(QST * Q_STAGE <= M_BARS, "");
DEVI uint32_t q_stage(int kb) { return ((kb + 3) & 3) * Q_STAGE; }

struct Side { const unsigned char* pf[8]; const bf16 *lre, *lim, *ldt; };
DEVI float2 cmul(float2 a, float2 b) { return make_float2(a.x * b.x - a.y * b.y, a.x * b.y + a.y * b.x); }
DEVI float2 cfma(float2 a, float2 b, float2 c) { return make_float2(fmaf(a.x, b.x, fmaf(-a.y, b.y, c.x)), fmaf(a.x, b.y, fmaf(a.y, b.x, c.y))); }
DEVI float4 f4(float2 a, float2 b) { return make_float4(a.x, a.y, b.x, b.y); }

DEVI void side_jobs(const Side& sd, int p) {
  const float dt = bf_round(expf(__bfloat162float(sd.ldt[p]))), re = __bfloat162float(sd.lre[p]), im = __bfloat162float(sd.lim[p]);
#pragma unroll
  for (int k = 0; k < 16; k++) g_agg[(4 + k) * DM + p] = ~0ull;
  if (p < CNT_Q) g_cnt[p * 32] = 0;
  if (p < 512) g_flag[p] = 0;
  asm volatile("" :: "f"(dt), "f"(re), "f"(im));
  const float ex = expf(dt * re);
  float sn, cs;
  {
    const double th = dt * im, t = th * 0.31830988618379069, e = fma(th, 0.31830988618379069, -t) - th * 1.9678676675182487e-17;
    sincospif((float)(t - 2.0 * rint(0.5 * t) + e), &sn, &cs);
  }
  const float2 lam = make_float2(ex * cs, ex * sn), mu = make_float2(lam.x, -lam.y);
  const float r = 2.f / (re * re + im * im);
  const float2 coef = make_float2(((lam.x - 1.f) * re + lam.y * im) * r, (lam.y * re - (lam.x - 1.f) * im) * r);
  const float2 m2 = cmul(mu, mu), m4 = cmul(m2, m2), m8 = cmul(m4, m4), m16 = cmul(m8, m8), m32 = cmul(m16, m16), m64 = cmul(m32, m32);
  const float2 m128 = cmul(m64, m64), m256 = cmul(m128, m128), m512 = cmul(m256, m256), one = make_float2(1.f, 0.f), zero = make_float2(0.f, 0.f);
  asm volatile("" :: "f"(m512.x));
  float4* t = g_tab + p;
#pragma unroll
  for (int c = 0; c < 4; c++) { t[4 * c * DM] = f4(mu, coef); t[(4 * c + 1) * DM] = f4(m8, m512); }
  t[2 * DM] = f4(zero, zero); t[3 * DM] = f4(one, one);
  t[6 * DM] = f4(m32, zero);  t[7 * DM] = f4(m128, m32);
  t[10 * DM] = f4(m32, m64);  t[11 * DM] = f4(m256, m64);
  t[14 * DM] = f4(m32, m64);  t[15 * DM] = f4(cmul(m128, m256), cmul(m32, m64));
}

DEVI void ldsm4(uint32_t* r, uint32_t a) {
  asm volatile("ldmatrix.sync.aligned.m8n8.x4.shared.b16 {%0, %1, %2, %3}, [%4];" : "=r"(r[0]), "=r"(r[1]), "=r"(r[2]), "=r"(r[3]) : "r"(a) : "memory");
}
template <int O>
DEVI void qkv_step(float* acc, const uint32_t* a, uint64_t dB, int add) {
  if constexpr (O == 0) rs_n64(acc, a, dB, add);
  if constexpr (O == 8) rs_n56(acc, a, dB + 1, add);
  if constexpr (O == 16) rs_n48(acc, a, dB + 2, add);
  if constexpr (O == 24) rs_n40(acc, a, dB + 3, add);
  if constexpr (O == 32) rs_n32(acc, a, dB + 4, add);
  if constexpr (O == 40) rs_n24(acc, a, dB + 5, add);
  if constexpr (O == 48) rs_n16(acc, a, dB + 6, add);
  if constexpr (O == 56) rs_n8(acc, a, dB + 7, add);
  acc += 32 - O / 2;
  rs_n64(acc, a, dB + 512, add);
  if constexpr (O == 0) rs_n88(acc + 32, a, dB + 1024, add);
  if constexpr (O == 8) rs_n96(acc + 32, a, dB + 1024, add);
  if constexpr (O > 8) rs_n64(acc + 32, a, dB + 1024, add);
  if constexpr (O == 16) rs_n40(acc + 64, a, dB + 1536, add);
  if constexpr (O == 24) rs_n48(acc + 64, a, dB + 1536, add);
  if constexpr (O == 32) rs_n56(acc + 64, a, dB + 1536, add);
  if constexpr (O == 40) rs_n64(acc + 64, a, dB + 1536, add);
  if constexpr (O == 48) rs_n72(acc + 64, a, dB + 1536, add);
  if constexpr (O == 56) rs_n80(acc + 64, a, dB + 1536, add);
}
DEVI void stg(void* a, uint32_t x) { *(uint32_t*)a = x; }
DEVI void stg(void* a, uint32_t x, uint32_t y) { *(uint2*)a = make_uint2(x, y); }
DEVI void stg(void* a, uint32_t x, uint32_t y, uint32_t z, uint32_t w) { *(uint4*)a = make_uint4(x, y, z, w); }
DEVI uint32_t hmul2(uint32_t a, uint32_t b) { uint32_t d; asm("mul.rn.f16x2 %0, %1, %2;" : "=r"(d) : "r"(a), "r"(b)); return d; }
DEVI uint32_t hadd2(uint32_t a, uint32_t b) { uint32_t d; asm("add.rn.f16x2 %0, %1, %2;" : "=r"(d) : "r"(a), "r"(b)); return d; }
DEVI uint32_t hmax2(uint32_t a, uint32_t b) { uint32_t d; asm("max.NaN.f16x2 %0, %1, %2;" : "=r"(d) : "r"(a), "r"(b)); return d; }
DEVI uint32_t hfma2(uint32_t a, uint32_t b, uint32_t c) { uint32_t d; asm("fma.rn.f16x2 %0, %1, %2, %3;" : "=r"(d) : "r"(a), "r"(b), "r"(c)); return d; }
DEVI uint32_t hsum2(uint32_t a, uint32_t b) { return hadd2(__byte_perm(a, b, 0x5410), __byte_perm(a, b, 0x7632)); }
template <int J>
DEVI void qkv_tile(int warp) {
  constexpr uint32_t sb = SB;
  asm volatile("// tile %0" ::"n"(J) : "memory");
  constexpr int O = 216 * J % 64, NK = J == 3 || J == 4 ? 3 : (J == 2 || J == 5), K0 = J == 2 ? 2 : 0;
  float acc[108];
  const uint32_t bars = sb + M_BARS;
  uint32_t lane = lane_id();
  const uint32_t a0 = sb + (warp * 16 + (lane & 15)) * 128 + (((lane >> 4) ^ (lane & 7)) << 4);
  const uint64_t dB0 = mkdesc(sb + Q_A, 8192, 1024, 1);
#pragma unroll
  for (int i = 0; i < 108; i++) asm volatile("" : "=f"(acc[i])::"memory");
  bar_sync(0, 768);
  uint32_t a[4][4];
  mbar_wait(bars + B_QFULL, 0);
  __syncwarp();
  ldsm4(a[0], a0 + q_stage(0));
#pragma unroll 1
  for (int kb = 0; kb < 9; kb++) {
    const uint32_t done = bars + B_QEMPTY + 8 * ((kb - 1) & (QST - 1));
    const bool pause = kb == 5 && warp >= 4, rel = kb >= 1 && lane == 0;
    if (pause) {
      wg_wait<0>();
      if (rel) mbar_arrive(done);
      bar_sync(1, 256);
    }
    const uint32_t aa = a0 + q_stage(kb);
    const uint64_t dB = dB0 + (q_stage(kb) >> 4);
#pragma unroll
    for (int ks = 0; ks < 4; ks++) {
      if (ks == 3 && kb == 8 && warp < 4) bar_arrive(1, 256);
      if (ks == 3) {
        if (kb < 8) mbar_wait(bars + B_QFULL + 8 * ((kb + 1) & (QST - 1)), ((kb + 1) / QST) & 1);
        __syncwarp();
      }
      ldsm4(a[(ks + 1) & 3], ks < 3 ? aa ^ (32 * ks + 32) : a0 + q_stage(kb + 1));
      wg_fence();
      qkv_step<O>(acc, a[ks], dB + 128 * ks, ks ? 1 : kb);
      wg_commit();
      wg_wait<2>();
      if (ks == 1) {
        if (rel && !pause) mbar_arrive(done);
        __syncwarp();
      }
    }
  }
  lane = lane_id();
  const uint32_t g = lane >> 2, c = lane & 3, slab = (((cta_id() - 4) >> 3) + (warp >> 2) * 16) * 4 + (warp & 3);
  wg_wait<0>();
#pragma unroll
  for (int i = 0; i < 108; i++) asm volatile("" : "+f"(acc[i])::"memory");
  if (elect_one()) mbar_arrive(bars + B_RING);
  __syncwarp();

  constexpr uint32_t KS = 0x35713571u;
  const uint32_t pm = PM >> (2 * (slab & 7)), ks[2] = {pm & 1 ? KS - 0x24002400u : KS, pm & 2 ? KS - 0x24002400u : KS};
  uint32_t kn[3];
  if (warp >= 4) mbar_wait(bars + B_PUB, 0);
  __syncwarp();
#pragma unroll
  for (int a = 0; a < 3; a++) {
    const int slot = 12 * J + 4 * a, type = slot >> 5;
    uint32_t v[9][2], w[4][2], t[2], n[4];
    unsigned char* ip = g_q + slot * HQ + slab * 640;
    unsigned char* mp = g_kv + (slot & 31) * HS + (type == 2 ? 8192 : 0) + (slab >> 4) * 16384 + (slab & 15) * 256 + lane * 4;
#pragma unroll
    for (int hh = 0; hh < 4; hh++) {
#pragma unroll
      for (int r = 0; r < 2; r++) {
#pragma unroll
        for (int b = hh ? 2 * hh + 1 : 0; b < 2 * hh + 3; b++) v[b][r] = pack_h2(acc[4 * (9 * a + b) + 2 * r], acc[4 * (9 * a + b) + 2 * r + 1]);
        w[hh][r] = c < hh ? v[2 * hh + 2][r] : v[2 * hh][r];
        if (type) {
          stg(mp + hh * HS + r * 128, type == 1 ? hmul2(v[2 * hh + 1][r], ks[r]) : v[2 * hh + 1][r]);
          stg(mp + hh * HS + r * 128 + 4096, type == 1 ? hmul2(w[hh][r], ks[r]) : w[hh][r]);
        }
      }
      if (!type) stg(ip + hh * HQ + lane * 16, v[2 * hh + 1][0], v[2 * hh + 1][1], w[hh][0], w[hh][1]);
      if (hh == 3 && slab == 1000 + 4 * a + hh) __trap();
      if (type < 2)
        n[hh] = hsum2(hfma2(v[2 * hh + 1][0], v[2 * hh + 1][0], hmul2(w[hh][0], w[hh][0])), hfma2(v[2 * hh + 1][1], v[2 * hh + 1][1], hmul2(w[hh][1], w[hh][1])));
    }
#pragma unroll
    for (int r = 0; r < 2; r++) t[r] = c < 2 ? (c < 1 ? v[2][r] : v[4][r]) : (c < 3 ? v[6][r] : v[8][r]);
    if (type < 2) {
#pragma unroll
      for (int i = 0; i < 2; i++) n[i] = hadd2(c & 2 ? n[i + 2] : n[i], __shfl_xor_sync(~0u, c & 2 ? n[i] : n[i + 2], 2));
      n[0] = hadd2(c & 1 ? n[1] : n[0], __shfl_xor_sync(~0u, c & 1 ? n[0] : n[1], 1));
      n[0] = hadd2(n[0], hsum2(hmul2(t[0], t[0]), hmul2(t[1], t[1])));
    }
    if (type == 1) { kn[a - K0] = n[0]; t[0] = hmul2(t[0], ks[0] - 0x04000400u); t[1] = hmul2(t[1], ks[1] - 0x04000400u); }
    if (type) stg(g_tail + (slot - 32 + c) * HT + slab * 64 + g * 8, t[0], t[1]);
    else stg(ip + c * HQ + 512 + g * 16, t[0], n[0], t[1], n[0] >> 16);
  }
  if constexpr (NK > 0) {
    uint32_t m = hmax2(kn[NK - 1], __byte_perm(kn[NK - 1], 0, 0x1032));
    if (NK == 3) {
      const uint32_t y = hmax2(__byte_perm(kn[0], kn[1], 0x5410), __byte_perm(kn[0], kn[1], 0x7632));
      m = hmax2(g & 1 ? m : y, __shfl_xor_sync(~0u, g & 1 ? y : m, 4));
    } else {
      m = hmax2(m, __shfl_xor_sync(~0u, m, 4));
    }
    m = hmax2(m, __shfl_xor_sync(~0u, m, 8));
    m = hmax2(m, __shfl_xor_sync(~0u, m, 16));
    if (g < NK) stg(g_knorm + (12 * J + 4 * K0 - 32 + (g & 1) * 8 + (g & 2) * 2 + c) * 128 + slab, g & 2 ? m >> 16 : m & 0xFFFF);
  }
  asm volatile("// tile %0" ::"n"(J) : "memory");
}

struct Maps { CUtensorMap B, X, H, Hs, Cre, Cim, Wo, WoT, Xq, W4, W5; };

DEVI void qkv_role(int warp, int j) {
  constexpr uint32_t bars = SB + M_BARS;
  reg_inc<160>();
  switch ((0x76032154u >> (4 * j)) & 7) {
    case 0: qkv_tile<5>(warp); break;
    case 1: qkv_tile<2>(warp); break;
    case 2: qkv_tile<3>(warp); break;
    case 3: qkv_tile<4>(warp); break;
    case 4: qkv_tile<0>(warp); break;
    case 5: qkv_tile<1>(warp); break;
    case 6: qkv_tile<6>(warp); break;
    default: qkv_tile<7>(warp); break;
  }
  __syncwarp();
  reg_dec<40>();
  if (elect_one()) mbar_arrive(bars + B_REL + 8 * (warp >> 2));
}
DEVI void qkv_load(const Maps& m, int t, int kb) {
  const int j = t & 7, c0 = (216 * j) >> 6, nch = ((216 * j + 215) >> 6) - c0 + 1;
  const uint32_t dst = SB + q_stage(kb), bar = SB + M_BARS + B_QFULL + 8 * (kb & (QST - 1));
  mbar_expect(bar, Q_A + nch * 8192);
  tma3(dst, &m.Xq, kb * 64, (t >> 3) * 64, 0, bar);
  tma3(dst + Q_A, nch == 4 ? &m.W4 : &m.W5, 0, kb * 64, c0, bar);
}
DEVI void qkv_producer(const Maps& m, const Side& sd, int t) {
#pragma unroll 1
  for (int kb = QST - 1; kb < 9; kb++) {
    if (kb >= QST) mbar_wait(SB + M_BARS + B_QEMPTY + 8 * (kb & (QST - 1)), (kb / QST - 1) & 1);
    if (kb >= QST) qkv_load(m, t, kb);
    if (kb == QST - 1) {
      l2_prefetch(sd.pf[6] + t * 18432, 18432);
      l2_prefetch(sd.pf[7] + 256 * 3456 + t * 8640, 8640);
    }
    if (kb == 8) {
      l2_prefetch(sd.pf[0] + t * 18432, 18432);
#pragma unroll
      for (int i = 1; i < 3; i++) l2_prefetch(sd.pf[i] + t * 5184, 5184);
    }
  }
#pragma unroll
  for (int i = 3; i < 6; i++) l2_prefetch(sd.pf[i] + t * 5184, 5184);
}

DEVI uint32_t ex2_mufu(uint32_t x) { uint32_t y; asm("ex2.approx.f16x2 %0, %1;" : "=r"(y) : "r"(x)); return y; }
DEVI uint32_t hfma2r(uint32_t a, uint32_t b, uint32_t c) { uint32_t d; asm("fma.rn.relu.f16x2 %0, %1, %2, %3;" : "=r"(d) : "r"(a), "r"(b), "r"(c)); return d; }
DEVI uint32_t ex2_fma(uint32_t y, uint32_t c3) {
  const uint32_t t = hfma2r(y, 0x02000200u, 0u);
  const uint32_t f = hfma2(t, 0xF800F800u, y);
  uint32_t p = hfma2(f, c3, 0x47c047c0u);
  p = hfma2(p, f, 0x298c298cu);
  p = hfma2r(p, f, 0x08000800u);
  return __funnelshift_l(t, t, 10) + p;
}

DEVI unsigned char* o_main(int row, int h) { return g_O + (h >> 2) * O_BLK + (row >> 3) * 1024 + (h & 3) * 256 + (row & 7) * 16; }
DEVI unsigned char* o_tail(int row, int h) { return g_O + 8 * O_BLK + (row >> 3) * 1024 + h * 32; }

__device__ __noinline__ void attn_exact(const bf16* __restrict__ X, const bf16* __restrict__ W, uint32_t mask, unsigned char* smem) {
  const int h = (blockIdx.x - 4) >> 2, qb = blockIdx.x & 3;
  uint32_t* kv = (uint32_t*)(smem + A_BASE + A_SLOT);
  const int tid = threadIdx.x, slab = tid >> 4;
  const int qt = (slab >> 4) * 16 + qb * 4 + ((slab >> 2) & 3), row = qt * 64 + (slab & 3) * 16 + (tid & 15);
  float q[18], o[18];
#pragma unroll
  for (int i = 0; i < 18; i++) { q[i] = 0.f; o[i] = 0.f; }
#pragma unroll 1
  for (int d = 0; d < DM; d++) {
    const float x = __bfloat162float(X[row * DM + d]);
    const uint32_t* wq = (const uint32_t*)(W + d * 1728 + h * 18);
#pragma unroll
    for (int i = 0; i < 9; i++) { const uint32_t u = wq[i]; q[2 * i] += x * bf_lo(u); q[2 * i + 1] += x * bf_hi(u); }
  }
#pragma unroll
  for (int i = 0; i < 18; i++) q[i] = bf_round(q[i]);
  float m = -INFINITY, l = 0.f;
#pragma unroll 1
  for (int part4 = 0; part4 < 4; part4++) {
    bar_sync(1, 512);
#pragma unroll 1
    for (int kp = tid; kp < 1024; kp += 512) {
      const int key = kp >> 1, part = kp & 1;
      float a[18];
#pragma unroll
      for (int i = 0; i < 18; i++) a[i] = 0.f;
#pragma unroll 1
      for (int d = 0; d < DM; d++) {
        const float x = __bfloat162float(X[(part4 * 512 + key) * DM + d]);
        const uint32_t* w = (const uint32_t*)(W + d * 1728 + 576 + part * 576 + h * 18);
#pragma unroll
        for (int i = 0; i < 9; i++) { const uint32_t u = w[i]; a[2 * i] += x * bf_lo(u); a[2 * i + 1] += x * bf_hi(u); }
      }
#pragma unroll
      for (int i = 0; i < 9; i++) kv[key * 18 + part * 9 + i] = pack_b2(a[2 * i], a[2 * i + 1]);
    }
    bar_sync(1, 512);
#pragma unroll 1
    for (int key = 0; key < 512; key++) {
      float s = 0.f;
#pragma unroll
      for (int i = 0; i < 9; i++) { const uint32_t u = kv[key * 18 + i]; s += q[2 * i] * bf_lo(u) + q[2 * i + 1] * bf_hi(u); }
      s = bf_round(bf_round(s) * 0.23570226f);
      const float mn = fmaxf(m, s), al = (m == mn) ? 1.f : expf(m - mn), p = expf(s - mn);
      m = mn;
      l = l * al + p;
#pragma unroll
      for (int i = 0; i < 9; i++) { const uint32_t u = kv[key * 18 + 9 + i]; o[2 * i] = o[2 * i] * al + p * bf_lo(u); o[2 * i + 1] = o[2 * i + 1] * al + p * bf_hi(u); }
    }
  }
  const bool mine = (mask >> slab) & 1;
  const float inv = 1.f / l;
  const uint32_t own = pack_b2(o[16] * inv, o[17] * inv), other = __shfl_xor_sync(~0u, own, 1);
  if (mine) {
#pragma unroll
    for (int i = 0; i < 8; i++) st_relaxed(o_main(row, h) + (i & 2) * 64 + (i & 1) * 8 + (i >> 2) * 4, pack_b2(o[2 * i] * inv, o[2 * i + 1] * inv));
    st_relaxed(o_tail(row, h) + (row & 1) * 16 + (row & 6) * 2, (row & 1) ? __byte_perm(other, own, 0x7632) : __byte_perm(own, other, 0x5410));
  }
  __syncwarp();
  if (mine && (tid & 15) == 0) red_release(slab < 16 ? g_cnt + (CNT_O + qt) * 32 : g_flag + (qt - 16) * 32 + h, 1);
}

DEVI uint32_t q_row(uint32_t a, uint32_t l, uint32_t x, uint32_t n, float kk) {
  const float n2 = h_lo(n), b = sqrt_approx((n2 + 1e-6f) * kk) * 0.3416f + 0.004f;
  const uint32_t m = pack_h2(fminf(15.25f - b, fmaxf(-2.f, b - 13.5f)), 1.f);
  if (!(l & 2)) sts128(a, x, m, 0, n2 <= 1024.f && b <= 64.f ? (b > 14.375f ? 0x60000000u : 0x48000000u) : 0x7C000000u);
  fence_async_smem();
  __syncwarp();
  return m;
}
DEVI uint32_t q_addr(int warp, uint32_t l) { return SB + A_QT + warp * 256 + ((l * 4 & 0x70) | (l * 128 & 128)); }

struct KvDesc { uint64_t k[4], v[4]; };
DEVI void wait_qkv(int half8) {
  const unsigned* qcnt = g_cnt + (CNT_Q + half8 + (((cta_id() - 4) >> 2) + 32 * min(lane_id(), 2)) / 12) * 32;
  int k = 0;
#pragma unroll 1
  while (!__all_sync(~0u, ld_acquire(qcnt) >= 16))
    if (++k == (1 << 22)) __trap();
  __syncwarp();
}
DEVI void kv_role() {
  constexpr uint32_t sb = SB, bars = sb + M_BARS;
  const uint32_t tdst = sb + A_BASE + 16384 + (lane_id() >> 3) * 256 + (lane_id() & 7) * 16;
#pragma unroll 1
  for (int r = 0; r < 3; r++) {
    const uint32_t cta = cta_id() - 4, h = cta >> 2;
    const unsigned char *kv = g_kv + (h * HS + (r & 1) * 65536), *tp = g_tail + (h * HT + (r & 1) * 4096 + lane_id() * 8);
    asm volatile("" : "+l"(tp));
    if (r < 2) {
      wait_qkv(8 * r);
      if (elect_one()) mbar_arrive(bars + (r ? B_SEEN : B_GO));
      fence_async_gmem();
      if (r) {
        const uint4 v = *(const uint4*)(g_knorm + (h * 128 + lane_id() * 4));
        if (elect_one()) {
          mbar_expect(bars + B_Q2, 10240);
          bulk_load(sb + A_Q2, g_q + (h * HQ + (64 + (cta & 3) * 16) * 640), 10240, bars + B_Q2);
        }
        sts32(bars + W_KMAX, __float_as_uint(h_lo(__reduce_max_sync(~0u, max(max(v.x, v.y), max(v.z, v.w)))) + 1e-6f));
      } else {
        mbar_wait(bars + B_RING, 0);
      }
    } else {
      mbar_wait(bars + B_GATE, 0);
      mbar_wait(bars + B_DONE, 0);
      const uint32_t l = lane_id();
      if (l < 4) red_release(g_cnt + (CNT_O + (cta & 3) * 4 + l) * 32, 4 - __popc((lds32(bars + W_MASK) >> (4 * l)) & 15));
      __syncwarp();
    }
    uint32_t s8, ta = tdst;
    asm volatile("mov.u32 %0, 0;" : "=r"(s8));
#pragma unroll 1
    do {
      asm volatile("" : "+l"(tp), "+r"(ta));
      uint2 kt[4], vt[4];
#pragma unroll
      for (int u = 0; u < 4; u++) { kt[u] = ldg64(tp + u * 256); vt[u] = ldg64(tp + u * 256 + 32 * HT); }
      if (r) mbar_wait(bars + B_KVEMPTY + s8, 0);
      if (elect_one()) {
        mbar_expect(bars + B_KVFULL + s8, 16384);
        bulk_load(sb + A_BASE + s8 * (A_SLOT / 8), kv, 16384, bars + B_KVFULL + s8);
      }
#pragma unroll
      for (int u = 0; u < 4; u++) {
        const uint32_t a = ta + u * 1024;
        sts32(a, kt[u].x); sts32(a + 128, kt[u].y); sts32(a + 8, vt[u].x); sts32(a + 136, vt[u].y);
      }
      fence_async_smem();
      __syncwarp();
      if (elect_one()) mbar_arrive(bars + B_KVFULL + s8);
      kv += 16384; tp += 1024; ta += A_SLOT; s8 += 8;
    } while (s8 != 32);
  }
  if (elect_one()) {
    mbar_wait(bars + B_KVEMPTY, 1);
    mbar_arrive(bars + B_FREE);
    mbar_wait(bars + B_KVEMPTY + 16, 1);
    mbar_arrive(bars + B_O1E);
  }
}

DEVI void attn_role(unsigned char* smem, int warp, const bf16* __restrict__ X, const bf16* __restrict__ W, const KvDesc& dt) {
  const int tid = threadIdx.x, lane = tid & 31, g = lane >> 2, c = lane & 3;
  constexpr uint32_t sb = SB, bars = sb + M_BARS;
  mbar_wait(bars + B_GO, 0);
  uint32_t q[4], qn;
  {
    const int cta = cta_id() - 4, h = cta >> 2, qb = cta & 3;
    const unsigned char* qp = g_q + h * HQ + (qb * 16 + warp) * 640;
    const uint2 v = *(const uint2*)(g_knorm + h * 128 + lane * 2);
    const uint4 a = *(const uint4*)(qp + lane * 16);
    const uint2 at = *(const uint2*)(qp + 512 + g * 16 + (c & 1) * 8);
    q[0] = a.x; q[1] = a.y; q[2] = a.z; q[3] = a.w; qn = at.y;
    q_row(q_addr(warp, lane), lane, at.x, at.y, h_lo(__reduce_max_sync(~0u, max(v.x, v.y))) + 1e-6f);
    if (elect_one()) mbar_arrive(bars + B_QOK);
  }
  const uint64_t dq = mkdesc(sb + A_QT + (warp >> 2) * 1024, 0, 128, 0);
  __syncwarp();
  uint32_t o[6], o1[6];
#pragma unroll
  for (int i = 0; i < 6; i++) o[i] = o1[i] = 0;
#pragma unroll 1
  for (uint32_t it = 0; it < 128;) {
    uint32_t c3, par, lim, off;
    asm volatile("{\n.reg .b32 x;\nld.volatile.shared.v4.u32 {%0, %1, %2, x}, [%3];\n}" : "=r"(c3), "=r"(par), "=r"(lim) : "r"(bars + W_CONST + (it >> 1)));
    asm volatile("mov.u32 %0, 0;" : "=r"(off));
#pragma unroll 1
    do {
      mbar_wait(bars + B_KVFULL + off, par);
      const uint64_t dk = *(const uint64_t*)((const char*)dt.k + off), dv = *(const uint64_t*)((const char*)dt.v + off);
#pragma unroll
      for (int t = 0; t < 2; t++) {
        uint32_t s[32];
        wg_fence();
        qk_n128_z(s, q[0], q[1], q[2], q[3], dk + t * 128);
        qk_n128_ss(s, dq, dk + (t * 128 + 1024 - (256 << 16)));
        wg_commit();
        if (!t && elect_one()) mbar_arrive(bars + B_KVEMPTY - 8 + off);
        wg_wait<0>();
#pragma unroll
        for (int k = 0; k < 32; k++) asm volatile("" : "+r"(s[k])::"memory");
#pragma unroll
        for (int u = 0; u < 4; u++) {
#pragma unroll
          for (int i = 0; i < 8; i++) {
            const int k = u * 8 + i;
            s[k] = ((PM >> (k >> 1)) & 1) ? ex2_fma(s[k], c3) : ex2_mufu(s[k]);
          }
#pragma unroll
          for (int i = 0; i < 8; i++) asm volatile("" : "+r"(s[u * 8 + i])::"memory");
          wg_fence();
#pragma unroll
          for (int i = 0; i < 2; i++) {
            const int k = u * 2 + i;
            pv_n24(o, s[4 * k], s[4 * k + 1], s[4 * k + 2], s[4 * k + 3], dv + (t * 128 + k * 16));
          }
        }
        wg_commit();
        wg_wait<0>();
      }
      off += 8;
    } while (off != lim);
    if (elect_one()) mbar_arrive(bars + B_KVEMPTY + 24);
    it += 32;
#pragma unroll
    for (int i = 0; i < 6; i++) asm volatile("" : "+r"(o[i])::"memory");
    if (it & 32) {
      if (it == 32) {
        mbar_wait(bars + B_KVFULL, 1);
        const uint32_t l = lane_id(), a = q_addr(warp, l);
        const uint2 old = lds64(a);
        __syncwarp();
        const uint32_t m = q_row(a, l, old.x, qn, __uint_as_float(lds32(bars + W_KMAX)));
        if (__any_sync(~0u, m != old.y)) {
          const float e = ex2_approx(h_lo(m) - h_lo(old.y));
          const uint32_t f = pack_h2(e, e), f2 = __shfl_xor_sync(~0u, f, 1), f0 = l & 1 ? f2 : f, f1 = l & 1 ? f : f2;
#pragma unroll
          for (int i = 0; i < 6; i++) o[i] = hmul2(o[i], (i & 1) ? f1 : f0);
        }
        __syncwarp();
      }
#pragma unroll
      for (int i = 0; i < 6; i++) { o1[i] = o[i]; o[i] = 0; }
    } else {
      const uint32_t pass = it >> 7, t = lane_id(), cc = t & 3, cta = cta_id() - 4, h = cta >> 2, qb = cta & 3;
      const uint32_t a = q_addr(warp, t), lim = lds32(a + 12);
      if (!pass) {
        const uint32_t qa = sb + A_Q2 + warp * 640;
        mbar_wait(bars + B_Q2, 0);
        asm volatile("ld.shared.v4.u32 {%0, %1, %2, %3}, [%4];" : "=r"(q[0]), "=r"(q[1]), "=r"(q[2]), "=r"(q[3]) : "r"(qa + t * 16) : "memory");
        const uint2 at = lds64(qa + 512 + ((t * 4 & 0x70) | (t * 8 & 8)));
        __syncwarp();
        q_row(a, t, at.x, at.y, __uint_as_float(lds32(bars + W_KMAX)));
      }
      uint32_t w[6], t0, t1;
#pragma unroll
      for (int i = 0; i < 6; i++) { w[i] = hadd2(o[i], o1[i]); o[i] = 0; }
      const uint32_t ls = __shfl_sync(~0u, __byte_perm(w[4], w[5], 0x5410), t | 3);
      const float i0 = rcp_approx(h_lo(ls)), i1 = rcp_approx(h_hi(ls));
#pragma unroll
      for (int i = 0; i < 6; i++) w[i] = pack_b2(h_lo(w[i]) * ((i & 1) ? i1 : i0), h_hi(w[i]) * ((i & 1) ? i1 : i0));
      {
        const uint32_t rows = (pass * 128 + qb * 32 + warp * 2) * 1024;
        const bool sw = cc >= (h & 3);
        unsigned char* op = g_O + ((h >> 2) * O_BLK + rows + (h & 3) * 256) + ((((t - h) & 3) * 72 & 0x88) | (t * 4 & 0x70));
        st_relaxed2(op, sw ? w[2] : w[0], sw ? w[0] : w[2]);
        st_relaxed2(op + 1024, sw ? w[3] : w[1], sw ? w[1] : w[3]);
        asm volatile("movmatrix.sync.aligned.m8n8.trans.b16 %0, %1;" : "=r"(t0) : "r"(w[4]));
        asm volatile("movmatrix.sync.aligned.m8n8.trans.b16 %0, %1;" : "=r"(t1) : "r"(w[5]));
        op = g_O + (8 * O_BLK + rows + h * 32 - 64) + t * 4;
        if ((t & 24) == 16) { st_relaxed(op, t0); st_relaxed(op + 1024, t1); }
        __syncwarp();
      }
      uint32_t e = habs_max(habs_max(habs_max(w[0], w[1]), habs_max(w[2], w[3])), cc == 2 ? habs_max(w[4], w[5]) : 0u);
      e = __reduce_max_sync(~0u, habs_max(e, e >> 16) & 0x7FFFu);
      const uint32_t sum = t & 1 ? ls & 0xFFFF0000u : ls << 16;
      const bool bad = __any_sync(~0u, sum - lim >= 0x7C000000u - lim) | (e - 0x3A80u >= 0x7F80u - 0x3A80u);
      if (pass && !bad && t == 16) red_relaxed(g_flag + (qb * 4 + (warp >> 2)) * 32 + h, 1);
      if (bad && elect_one()) asm volatile("red.shared.or.b32 [%0], %1;" ::"r"(bars + W_MASK), "r"(1u << (pass * 16 + warp)) : "memory");
      __syncwarp();
      if (!pass && elect_one()) mbar_arrive(bars + B_DONE);
      __syncwarp();
    }
  }
  bar_sync(1, 512);
  const uint32_t mask = lds32(bars + W_MASK);
  if (mask) attn_exact(X, W, mask, smem);
  if (cta_id() < 121 && warp < 9) {
    const uint32_t l = lane_id(), a = o_block(warp) + l * 32 + (l & 28);
    uint32_t m = 0;
    mbar_wait(bars + B_O2T + 8 * warp, 0);
#pragma unroll
    for (int i = 0; i < 10; i++) m = max(m, lds32(a + i * 1024));
    any_empty(3, 416, m);
  }
}

DEVI void watch_role(unsigned char* smem, int tb, int part) {
  constexpr uint32_t bars = SB + M_BARS;
  const int lane = threadIdx.x & 31, row0 = 1024 + min(tb * 80, 944), cutr = 64 - (row0 & 63);
  const int row = part ? row0 + cutr : row0, n = part ? 80 - cutr : cutr;
  const unsigned* src = g_flag + ((row - 1024) >> 6) * 32 + lane;
  const uint32_t need = lane < 8 ? 15u << (4 * lane) : ~0u, dst = o_block(lane) + (row - row0) * 128, bar = bars + B_O2T + 8 * lane;
  uint32_t* q = (uint32_t*)(smem + M_BARS + W_QUEUE);
  bool todo = lane < 9;
  mbar_wait(bars + B_O1E, 0);
#pragma unroll 1
  for (int k = 0; k < (1 << 23) && __any_sync(~0u, todo); k++) {
    const uint32_t seen = __ballot_sync(~0u, ld_acquire(src) == 4);
    __syncwarp();
    if (todo && (seen & need) == need) {
      fence_async_gmem();
      mbar_expect(bar, n * 128);
      bulk_load(dst, g_O + lane * O_BLK + row * 128, n * 128, bar);
      todo = false;
      if (lane < 8 && atomicAdd(q + 2 + lane, 1u)) {
        const uint32_t e = atomicAdd(q + 1, 1u);
        atomicOr(q, (lane + 1) << (4 * e));
        mbar_arrive(bars + B_O2 + 8 * e);
      }
    }
  }
}

constexpr int F_STAGE = 49152, F_NS = 4;
DEVI int h_slot(bool side, int n) { return side ? (9 * n + 8) % F_NS : (9 * n + 8) % NS; }
DEVI uint32_t h_stage(bool side, int u, int n) { return SB + (u == 3 ? F_NS * F_STAGE : (side ? h_slot(side, n) * F_STAGE + u * 16384 : h_slot(side, n) * S_STAGE)); }
DEVI int scan_tile(int cta, int u, int i) { return 144 * i + (cta < 4 ? 4 * cta + u : 12 + cta); }
DEVI int out_row(int cta, int i) { return cta < 4 ? (4 * i + cta) * 256 : ((cta - 4) >> 2) * 64; }
DEVI int out_col(int cta) { return cta < 4 ? 512 : (cta & 3) * 128; }

template <bool SIDE>
DEVI void producer_role(const Maps& m, const Side& sd) {
  constexpr uint32_t sb = SB, bars = sb + M_BARS, ns = SIDE ? F_NS : NS, na = SIDE ? 4 : 1, stride = SIDE ? F_STAGE : S_STAGE;
  const int cta = cta_id();
  if (!SIDE) qkv_producer(m, sd, cta - 4);
  uint32_t s8, ph = 1;
  asm volatile("mov.u32 %0, 0;" : "=r"(s8));
  auto next = [&](uint32_t bytes) {
    mbar_wait(bars + B_EMPTY + s8, ph);
    if (bytes) mbar_expect(bars + B_FULL + s8, bytes);
    return sb + s8 * (stride / 8);
  };
  auto step = [&]() { s8 += 8; if (s8 == 8 * ns) { s8 = 0; ph ^= 1; } };
#pragma unroll 1
  for (int i = 0; i < 2; i++) {
    const int t = scan_tile(cta, 0, i), chunk = t / 18, grp = t - chunk * 18;
    if (!SIDE) {
      if (i) mbar_wait(bars + B_SEEN, 0);
      else mbar_wait(bars + B_QEMPTY + 8, 1);
    }
#pragma unroll 1
    for (int k = 0; k < DM; k += 64) {
      if (!SIDE && !i) {
        if (k == 128) mbar_wait(bars + B_QEMPTY + 16, 1);
        if (k == 256) mbar_wait(bars + B_QEMPTY + 24, 1);
        if (k == 128) mbar_wait(bars + B_PUB, 0);
        if (k == 256) mbar_wait(bars + B_QOK, 0);
      }
      const uint32_t dst = next((na + 2) * 8192);
      tma5(dst + na * 8192, &m.X, k, 0, 0, 0, chunk, bars + B_FULL + s8);
#pragma unroll
      for (int a = 0; a < na; a++) tma4(dst + a * 8192, &m.B, k, 0, 0, (grp + a) * 4, bars + B_FULL + s8);
      step();
    }
  }
#pragma unroll 1
  for (int i = 0; i < 1 + SIDE; i++) {
    const int row = out_row(cta, i), col = out_col(cta);
    uint32_t h8 = s8;
    auto load_h = [&](uint32_t s, int k) {
#pragma unroll
      for (int a = 0; a < na; a++) tma2(sb + s * (stride / 8) + a * 8192, &m.H, row + 64 * a, k, bars + B_FULL + s);
    };
#pragma unroll 1
    for (int k = 0; k < 2 * DM; k += 64) {
      const uint32_t dst = next((na + 2) * 8192);
      tma2(dst + na * 8192, k < DM ? &m.Cre : &m.Cim, k < DM ? k : k - DM, col, bars + B_FULL + s8);
      if (k >= 64 * ns) load_h(s8, k);
      step();
      if (k == 64 * (ns - 1)) {
        wait_count(g_cnt + (CNT_H + (row >> 7)) * 32, 18);
        if (SIDE) wait_count(g_cnt + (CNT_H + (row >> 7) + 1) * 32, 18);
        fence_async_gmem();
        if (cta == 131) {
#pragma unroll 1
          for (int n = CNT_Q; n <= CNT_SIDE; n++) g_cnt[n * 32] = 0;
        }
#pragma unroll 1
        for (int k0 = 0; k0 < 64 * ns; k0 += 64) {
          load_h(h8, k0);
          h8 = h8 == 8 * (ns - 1) ? 0 : h8 + 8;
        }
      }
    }
  }
  if (SIDE || cta >= 121) return;
  const int tb = (cta - 4) / 9, fc = cta - 4 - tb * 9, row = min(tb * 80, 944);
#pragma unroll 1
  for (int k = 0; k < NS; k++) { next(0); step(); }
  mbar_expect(bars + B_WO, 9 * 8192);
  tma5(sb, &m.Wo, fc * 64, 0, 0, 0, 0, bars + B_WO);
  tma3(sb + 8 * 8192, &m.WoT, fc * 64, 0, 0, bars + B_WO);
  wait_count(g_cnt + (CNT_O + (row >> 6)) * 32, 128);
  wait_count(g_cnt + (CNT_O + (row >> 6) + 1) * 32, 128);
  fence_async_gmem();
#pragma unroll
  for (int k = 0; k < 9; k++) {
    if (k == 6) mbar_wait(bars + B_FREE, 0);
    mbar_expect(bars + B_O1 + 8 * k, 10240);
    bulk_load(o_block(k), g_O + (k * O_BLK + row * 128), 10240, bars + B_O1 + 8 * k);
  }
}

DEVI void publish_role(const Maps& m) {
  constexpr uint32_t bars = SB + M_BARS;
  const int cta = cta_id();
  const bool side = cta < 4;
#pragma unroll 1
  for (int n = 0; n < 2; n++) {
    const int t = scan_tile(cta, 0, n), chunk = t / 18, grp = t - chunk * 18;
    mbar_wait(bars + B_H, n);
#pragma unroll 1
    for (int u = 0; u < (side ? 4 : 1); u++) tma_store4(&m.Hs, h_stage(side, u, n), 0, (grp + u) * 32, chunk * 2, 0);
    asm volatile("cp.async.bulk.commit_group;" ::: "memory");
    asm volatile("cp.async.bulk.wait_group.read 0;" ::: "memory");
    mbar_arrive_n(bars + B_EMPTY + 8 * h_slot(side, n), side ? 16 : 4);
    asm volatile("cp.async.bulk.wait_group 0;" ::: "memory");
    fence_async_gmem();
    red_release(g_cnt + (CNT_H + chunk) * 32, side ? 4 : 1);
  }
}

struct Pipe { uint64_t d0, d; uint32_t stride, ns8, st, ph; };

template <bool TA, int NK, bool SCAN>
DEVI void mainloop(float (&acc)[64], Pipe& p, uint32_t oa, uint32_t ob, uint32_t oa2, uint32_t ob2, uint32_t cnt) {
  constexpr uint32_t bars = SB + M_BARS;
  uint32_t prev = (uint32_t)(B_SPARE - B_EMPTY);
  auto block = [&](bool first) {
    mbar_wait(bars + B_FULL + p.st, p.ph);
    const uint64_t dA = p.d + oa, dB = p.d + ob, dA2 = p.d + oa2, dB2 = p.d + ob2;
    wg_fence();
#pragma unroll
    for (int ks = 0; ks < 4; ks++) {
      if constexpr (TA) { mma_n64_ta(acc, dA + ks * 128, dB + ks * 2); mma_n64_ta(acc + 32, dA2 + ks * 128, dB2 + ks * 2); }
      else if (first && !ks) { mma_n64_z(acc, dA, dB); mma_n64_z(acc + 32, dA2, dB2); }
      else { mma_n64(acc, dA + ks * 2, dB + ks * 2); mma_n64(acc + 32, dA2 + ks * 2, dB2 + ks * 2); }
      if (ks == 1) { wg_commit(); if (p.ns8 == 8 * NS) wg_wait<0>(); wg_fence(); }
    }
    wg_commit();
    if (p.ns8 == 8 * NS) wg_wait<0>();
    if (!first) {
      wg_wait<2>();
      if (elect_one()) { if (SCAN) mbar_arrive(bars + B_EMPTY + prev); else mbar_arrive_n(bars + B_EMPTY + prev, cnt); }
    }
    prev = p.st;
    p.st += 8; p.d += p.stride;
    if (p.st == p.ns8) { p.st = 0; p.ph ^= 1; p.d = p.d0; }
  };
  if (SCAN) {
    block(true);
  } else {
#pragma unroll
    for (int i = 0; i < 64; i++) asm volatile("" : "+f"(acc[i])::"memory");
  }
  uint32_t kb;
  asm volatile("mov.u32 %0, %1;" : "=r"(kb) : "n"(NK - SCAN));
#pragma unroll 1
  do block(false); while (--kb);
  wg_wait<0>();
  if (!SCAN && elect_one()) mbar_arrive_n(bars + B_EMPTY + prev, cnt);
#pragma unroll
  for (int i = 0; i < 64; i++) asm volatile("" : "+f"(acc[i])::"memory");
}
DEVI float4 ld_l2(const float4* p) {
  float4 v;
  asm volatile("ld.global.cg.v4.f32 {%0, %1, %2, %3}, [%4];" : "=f"(v.x), "=f"(v.y), "=f"(v.z), "=f"(v.w) : "l"(p));
  return v;
}
DEVI float2 ld_l2(const float2* p) {
  float2 v;
  asm volatile("ld.global.cg.v2.f32 {%0, %1}, [%2];" : "=f"(v.x), "=f"(v.y) : "l"(p));
  return v;
}

template <bool SWAP>
DEVI void gemm_role(unsigned char* smem, int warp, int u, const bf16* __restrict__ x, const bf16* __restrict__ dskip, float* __restrict__ out) {
  const int cta = cta_id();
  const bool side = cta < 4;
  constexpr uint32_t bars = SB + M_BARS;
  Pipe pp;
  pp.d0 = pp.d = mkdesc(SB, 16, 1024, 1);
  pp.stride = (side ? F_STAGE : S_STAGE) >> 4; pp.ns8 = 8 * (side ? F_NS : NS); pp.st = 0; pp.ph = 0;
#pragma unroll 1
  for (int n = 0; n < 2; n++) {
    const int tile = scan_tile(cta, u, n), chunk = tile / 18;
    const uint32_t p0 = (tile - chunk * 18) * 32 + warp * 8;
    const float4* tp = g_tab + (p0 + (lane_id() >> 2) + (lane_id() & 3) * 4 * DM);
    float4 t0;
    if (n) t0 = ld_l2(tp);
    float acc[64];
    mainloop<false, 9, true>(acc, pp, u * 512, side ? 2048 : 512, u * 512, side ? 2560 : 1024, 1);
    if (!n) {
      mbar_wait(bars + B_GATE, 0);
      t0 = ld_l2(tp);
    }
    uint64_t v[4];
    const int l = lane_id(), c = l & 3;
    const uint64_t* ap = g_agg + (uint32_t)((chunk + 3 - c) * DM + p0 + (l >> 2));
    auto poll = [&]() {
#pragma unroll
      for (int i = 0; i < 4; i++)
        asm volatile("{\n.reg .pred p;\nsetp.gt.s32 p, %2, %3;\n@p ld.relaxed.gpu.global.u64 %0, [%1];\n}"
                     : "+l"(v[i]) : "l"(ap - 4 * i * DM), "r"(chunk - c), "r"(4 * i) : "memory");
    };
    auto hi = [&](int i) { return (uint32_t)(v[i] >> 32); };
    constexpr int RE = SWAP ? 2 : 0, IM = SWAP ? 0 : 2;
    const float2 mu = make_float2(t0.x, t0.y);
#pragma unroll
    for (int t = 0; t < 32; t++) {
      const int i = 4 * (t >> 1) + (t & 1);
      const float ur = acc[i + RE], ui = acc[i + IM];
      acc[i + RE] = t0.z * ur - t0.w * ui;
      acc[i + IM] = -t0.z * ui - t0.w * ur;
    }
#pragma unroll
    for (int i = 0; i < 64; i++) asm volatile("" : "+f"(acc[i]));
    const float2 m8 = ld_l2((const float2*)(tp + DM));
    const float4 t2 = ld_l2(tp + 2 * DM);
    float2 a[4];
#pragma unroll
    for (int s = 0; s < 4; s++) a[s] = make_float2(acc[16 * s + RE], acc[16 * s + IM]);
#pragma unroll
    for (int j = 1; j < 8; j++)
#pragma unroll
      for (int s = 0; s < 4; s++) { const int i = 16 * s + 4 * (j >> 1) + (j & 1); a[s] = cfma(mu, a[s], make_float2(acc[i + RE], acc[i + IM])); }
    float2 t = cfma(m8, cfma(m8, cfma(m8, a[0], a[1]), a[2]), a[3]);
    t = cfma(make_float2(t2.x, t2.y), make_float2(__shfl_up_sync(~0u, t.x, 1), __shfl_up_sync(~0u, t.y, 1)), t);
    t = cfma(make_float2(t2.z, t2.w), make_float2(__shfl_up_sync(~0u, t.x, 2), __shfl_up_sync(~0u, t.y, 2)), t);
    asm volatile("" : "+l"(ap));
    if (c == 3 && chunk < 15)
      asm volatile("st.relaxed.gpu.global.u64 [%0], %1;" ::"l"(ap + 4 * DM), "l"((uint64_t)min(__float_as_uint(t.y), AGG_EMPTY - 1) << 32 | __float_as_uint(t.x)) : "memory");
#pragma unroll
    for (int i = 0; i < 4; i++) v[i] = 0;
    poll();
    float2 st[4];
    st[0] = make_float2(__shfl_up_sync(~0u, t.x, 1), __shfl_up_sync(~0u, t.y, 1));
    if (c == 0) st[0] = make_float2(0.f, 0.f);
#pragma unroll 1
    for (int k = 0; k < (1 << 22); k++) {
      if (!__any_sync(~0u, max(max(hi(0), hi(1)), max(hi(2), hi(3))) == AGG_EMPTY)) break;
      poll();
    }
    asm volatile("" : "+l"(tp));
    const float4 t3 = ld_l2(tp + 3 * DM);
    const float2 m512 = ld_l2((const float2*)(tp + DM) + 1);
    float2 hin = make_float2(__uint_as_float((uint32_t)v[3]), __uint_as_float(hi(3)));
#pragma unroll
    for (int i = 2; i >= 0; i--) hin = cfma(m512, hin, make_float2(__uint_as_float((uint32_t)v[i]), __uint_as_float(hi(i))));
    hin = cmul(hin, make_float2(t3.x, t3.y));
    hin.x += __shfl_xor_sync(~0u, hin.x, 1); hin.y += __shfl_xor_sync(~0u, hin.y, 1);
    hin.x += __shfl_xor_sync(~0u, hin.x, 2); hin.y += __shfl_xor_sync(~0u, hin.y, 2);
    st[0] = cfma(make_float2(t3.z, t3.w), hin, st[0]);
#pragma unroll
    for (int s = 1; s < 4; s++) st[s] = cfma(m8, st[s - 1], a[s - 1]);
    uint32_t wr[16], wi[16];
#pragma unroll
    for (int j = 0; j < 4; j++)
#pragma unroll
      for (int s = 0; s < 4; s++) {
        const int i = 16 * s + 4 * j;
        const float2 h0 = cfma(mu, st[s], make_float2(acc[i + RE], acc[i + IM]));
        st[s] = cfma(mu, h0, make_float2(acc[i + RE + 1], acc[i + IM + 1]));
        wr[4 * s + j] = pack_b2(h0.x, st[s].x); wi[4 * s + j] = pack_b2(h0.y, st[s].y);
      }
    bar_sync(2, side ? 512 : 128);
    const uint32_t l2 = lane_id(), hs = h_stage(side, u, n) + (l2 & 2) * 2048 + (warp * 8 + (l2 >> 2)) * 128;
#pragma unroll
    for (int s = 0; s < 4; s++) {
      const uint32_t a = hs + ((((l2 & 1) * 4 + s) ^ (l2 >> 2)) << 4);
      sts128(a, wr[4 * s], wr[4 * s + 1], wr[4 * s + 2], wr[4 * s + 3]);
      sts128(a + 8192, wi[4 * s], wi[4 * s + 1], wi[4 * s + 2], wi[4 * s + 3]);
    }
    fence_async_smem();
    __syncwarp();
    if (elect_one()) mbar_arrive(bars + B_H);
    __syncwarp();
  }
  if (u >= 2) return;
  const int lane = lane_id(), g = lane >> 2, c = lane & 3;
#pragma unroll 1
  for (int n = 0; n < 1 + side; n++) {
    const int row = out_row(cta, n) + u * 128 + warp * 16 + g, col = out_col(cta) + 2 * c;
    float acc[64];
#pragma unroll
    for (int v = 0; v < 2; v++) {
      const bf16 *xp = x + row * DM + col + (v ? (side ? 64 * DM : 64) : 0), *dp = dskip + col + (v && !side ? 64 : 0);
#pragma unroll
      for (int b = 0; b < 8; b++) {
        const uint32_t d = *(const uint32_t*)(dp + 8 * b);
        const uint32_t k0 = mul_b2(*(const uint32_t*)(xp + 8 * b), d), k1 = mul_b2(*(const uint32_t*)(xp + 8 * DM + 8 * b), d);
        float* a = acc + 32 * v + 4 * b;
        a[0] = bf_lo(k0); a[1] = bf_hi(k0); a[2] = bf_lo(k1); a[3] = bf_hi(k1);
      }
    }
    mainloop<true, 18, false>(acc, pp, u * 1024, side ? 2048 : 512, side ? u * 1024 + 512 : 0, side ? 2048 : 1024, 1 + side);
#pragma unroll
    for (int v = 0; v < 2; v++) {
      float* op = out + (size_t)row * 1152 + col + (v ? (side ? 64 * 1152 : 64) : 0);
#pragma unroll
      for (int b = 0; b < 8; b++) {
        const float* a = acc + 32 * v + 4 * b;
        *(float2*)(op + 8 * b) = make_float2(a[0], a[1]);
        *(float2*)(op + 8 * 1152 + 8 * b) = make_float2(a[2], a[3]);
      }
    }
  }
  if (side || cta >= 121) return;
  const int tb = (cta - 4) / 9, fc = cta - 4 - tb * 9;
  float* op = out + (size_t)(min(tb * 80, 944) + 2 * c) * 1152 + 576 + fc * 64 + warp * 16 + g;
  mbar_wait(bars + B_WO, 0);
#pragma unroll 1
  for (int half = 0; half < 2; half++) {
    float acc[40];
    uint32_t order = half ? 0 : 0x87654321u;
    const uint32_t full = bars + (half ? B_O2T : B_O1);
#pragma unroll 1
    for (uint32_t k = 0;; k++) {
#pragma unroll
      for (int i = 0; i < 40; i++) asm volatile("" : "=f"(acc[i])::"memory");
#pragma unroll 1
      for (int kb = 0; kb < 8; kb++) {
        if (!((order >> (4 * kb)) & 15)) {
          mbar_wait(bars + B_O2 + 8 * kb, 0);
          order = __reduce_or_sync(~0u, *(const volatile uint32_t*)(smem + M_BARS + W_QUEUE));
        }
        const int blk = ((order >> (4 * kb)) & 15) - 1;
        mbar_wait(full + 8 * blk, 0);
        const uint64_t dA = pp.d0 + blk * 512, dB = mkdesc(o_block(blk), 128, 1024, 0);
        wg_fence();
#pragma unroll
        for (int ks = 0; ks < 4; ks++) mma_n80_ta(acc, dA + ks * 128, dB + ks * 16, ks ? 1 : kb);
        wg_commit();
      }
      mbar_wait(full + 64, 0);
      wg_fence();
#pragma unroll
      for (int ks = 0; ks < 4; ks++) mma_n80_ta_tb(acc, pp.d0 + (8 * 512 + ks * 128), mkdesc(SB + A_Q2 + ks * 256, 128, 1024, 0));
      wg_commit();
      wg_wait<0>();
#pragma unroll
      for (int i = 0; i < 40; i++) asm volatile("" : "+f"(acc[i])::"memory");
      if (!half && elect_one()) mbar_arrive(bars + B_O1E);
#pragma unroll
      for (int b = 0; b < 10; b++) {
        op[(8 * b) * 1152] = acc[4 * b];
        op[(8 * b + 1) * 1152] = acc[4 * b + 1];
        op[(8 * b) * 1152 + 8] = acc[4 * b + 2];
        op[(8 * b + 1) * 1152 + 8] = acc[4 * b + 3];
      }
      uint32_t late = 0;
      if (half) {
        uint32_t m = 0;
        if (k) {
#pragma unroll 1
          for (int i = 0; i < 45; i++) m = max(m, max4(lds128(o_block(i / 5) + i % 5 * 2048 + (threadIdx.x & 127) * 16)));
        }
        late = __reduce_or_sync(~0u, any_empty(k ? 2 : 3, k ? 128 : 416, m));
      }
      if (!late) break;
      if (k == (1 << 20)) __trap();
      if (warp == 0 && elect_one()) {
        fence_async_smem();
        fence_async_gmem();
        mbar_expect(bars + B_QFULL + 8, 9 * 10240);
#pragma unroll 1
        for (int b = 0; b < 9; b++) bulk_load(o_block(b), g_O + (b * O_BLK + (1024 + min(tb * 80, 944)) * 128), 10240, bars + B_QFULL + 8);
      }
      mbar_wait(bars + B_QFULL + 8, k & 1);
    }
    op += 1024 * 1152;
  }
}

template <bool SWAP>
__global__ void __launch_bounds__(768, 1)
main_kernel(const __grid_constant__ Maps m, const __grid_constant__ Side sd, const bf16* __restrict__ X, const bf16* __restrict__ W,
            const __grid_constant__ KvDesc dt, const bf16* __restrict__ x, const bf16* __restrict__ dskip, float* __restrict__ out) {
  extern __shared__ __align__(1024) unsigned char smem[];
  const int warp = __reduce_max_sync(~0u, threadIdx.x >> 5);
  const bool side = blockIdx.x < 4;
  constexpr uint32_t bars = SB + M_BARS;
  if (warp < (side ? 0 : 8)) {
    qkv_role(warp, (blockIdx.x - 4) & 7);
  } else {
    reg_dec<40>();
    if (warp == 21 && !side && elect_one()) {
      mbar_init(bars + B_QFULL, 1);
      fence_mbar_init();
      qkv_load(m, cta_id() - 4, 0);
#pragma unroll
      for (int s = 0; s < QST; s++) { if (s) mbar_init(bars + B_QFULL + 8 * s, 1); mbar_init(bars + B_QEMPTY + 8 * s, 8); }
      fence_mbar_init();
    }
    __syncwarp();
    const int n = warp < 12 ? 2 : warp < 14 ? 16 : warp < 16 ? (side ? 16 : 4) : warp < 23 ? 1 : 5;
    if (warp >= 8 && elect_one()) {
#pragma unroll
      for (int i = 0; i < 4; i++) mbar_init(bars - 256 + 32 * warp + 8 * i, n);
      if (warp == 17) { mbar_init(bars + B_REL, 4); mbar_init(bars + B_REL + 8, 4); mbar_init(bars + B_GO, 9); mbar_init(bars + B_RING, 8); }
      fence_mbar_init();
    }
    if (warp == 16) {
      if (s2u(smem) != SB) __trap();
      const uint32_t l = threadIdx.x & 31;
      sts32(bars + W_MASK + l * 4, l < 16 ? 0 : (l & 2 ? 32 : (l & 1 ? (0x2200000 >> l) & 1 : 0x630d630du)));
    }
    bar_sync(0, 768);
    if (warp == 21 && !side && elect_one()) {
#pragma unroll 1
      for (int kb = 1; kb < QST; kb++) qkv_load(m, cta_id() - 4, kb);
    }
    __syncwarp();
  }
  if (warp < 16 && !side) {
    if (warp >= 8) {
      {
        const uint32_t t = cta_id() - 4;
        if (warp == 8 && (t & 6) == 6 && t < 72) {
          side_jobs(sd, ((t >> 3) * 2 + (t & 1)) * 32 + lane_id());
          __syncwarp();
          if (elect_one()) red_release(g_cnt + CNT_SIDE * 32, 1);
          __syncwarp();
        }
      }
      {
        const uint32_t cta = cta_id() - 4, h = cta >> 2, row = 1024 + (cta & 3) * 256, t = threadIdx.x & 255;
        const uint4 e = make_uint4(O_EMPTY, O_EMPTY, O_EMPTY, O_EMPTY);
        unsigned char* p = o_main(row, h) + (t >> 4) * 1024 + (t & 15) * 16;
        *(uint4*)p = e; *(uint4*)(p + 16384) = e;
        if (t < 64) *(uint4*)(o_tail(row, h) + (t >> 1) * 1024 + (t & 1) * 16) = e;
      }
      mbar_wait(bars + B_RING, 0);
      const uint32_t t = threadIdx.x & 255, sc = (PM >> ((t >> 3) & 15)) & 1 ? 0x22801400u : 0x00003800u;
#pragma unroll
      for (int i = 0; i < 4; i++) { sts32(SB + A_BASE + i * A_SLOT + 16384 + 4 + t * 16, sc); sts32(SB + A_BASE + i * A_SLOT + 16384 + 12 + t * 16, 0x00003C00u); }
      fence_async_smem();
      __syncwarp();
      if (elect_one()) mbar_arrive(bars + B_GO);
      __syncwarp();
      mbar_wait(bars + B_REL + 8, 0);
    }
    reg_inc<80>();
    attn_role(smem, warp, X, W, dt);
  } else if (warp >= 4 && warp < 20) {
    if (!side) {
      mbar_wait(bars + B_REL, 0);
      mbar_wait(bars + B_RING, 0);
    }
    reg_inc<104>();
    gemm_role<SWAP>(smem, warp & 3, 4 - (warp >> 2), x, dskip, out);
  } else if (warp < 4) {
    reg_dec<24>();
  } else if (warp == 20) {
    if (!side) kv_role();
  } else if (warp == 21) {
    if (elect_one()) { if (side) producer_role<true>(m, sd); else producer_role<false>(m, sd); }
  } else {
    if (elect_one()) {
      if (!side) {
        mbar_wait(bars + B_REL + 8 * (warp & 1), 0);
        red_release(g_cnt + (CNT_Q + 8 * (warp & 1) + ((cta_id() - 4) & 7)) * 32, 1);
        if (warp == 22) mbar_arrive(bars + B_PUB);
      }
      if (warp == 22) {
        wait_count(g_cnt + CNT_SIDE * 32, 18);
        mbar_arrive(bars + B_GATE);
      }
      mbar_wait(bars + B_GATE, 0);
      if (warp == 22) publish_role(m);
    }
    __syncwarp();
    if (!side && blockIdx.x < 121) watch_role(smem, (blockIdx.x - 4) / 9, warp & 1);
  }
}

typedef CUresult (*EncodeFn)(CUtensorMap*, CUtensorMapDataType, cuuint32_t, void*, const cuuint64_t*, const cuuint64_t*,
                             const cuuint32_t*, const cuuint32_t*, CUtensorMapInterleave, CUtensorMapSwizzle,
                             CUtensorMapL2promotion, CUtensorMapFloatOOBfill);

struct Setup {
  Maps m;
  const void* key[12];
  bool swap, ok;
};

bool encode(EncodeFn fn, CUtensorMap* m, const void* base, int rank, const cuuint64_t* dims, const cuuint64_t* strides,
            const cuuint32_t* box, CUtensorMapSwizzle sw) {
  const cuuint32_t es[5] = {1, 1, 1, 1, 1};
  return fn(m, CU_TENSOR_MAP_DATA_TYPE_BFLOAT16, rank, (void*)base, dims, strides, box, es, CU_TENSOR_MAP_INTERLEAVE_NONE, sw,
            CU_TENSOR_MAP_L2_PROMOTION_L2_256B, CU_TENSOR_MAP_FLOAT_OOB_FILL_NONE) == CUDA_SUCCESS;
}
bool encode2(EncodeFn fn, CUtensorMap* m, const void* base, uint64_t cols, uint64_t rows, uint64_t ld, uint32_t br) {
  const cuuint64_t d[2] = {cols, rows}, s[1] = {ld * 2};
  const cuuint32_t b[2] = {64, br};
  return encode(fn, m, base, 2, d, s, b, CU_TENSOR_MAP_SWIZZLE_128B);
}

template <typename K> void set_smem(K k, int bytes) {
  cudaFuncSetAttribute(k, cudaFuncAttributeMaxDynamicSharedMemorySize, bytes);
  cudaFuncSetAttribute(k, cudaFuncAttributePreferredSharedMemoryCarveout, 100);
}

}

extern "C" void kernel_launch(void* const* d_in, const int* in_sizes, int n_in, void* d_out, int out_size) {
  static Setup S = {};
  bool same = S.ok;
  for (int i = 0; i < 12; i++) same = same && S.key[i] == d_in[i];
  if (!same) {
    void* fp = nullptr;
    cudaDriverEntryPointQueryResult qr;
    cudaGetDriverEntryPoint("cuTensorMapEncodeTiled", &fp, cudaEnableDefault, &qr);
    EncodeFn fn = (EncodeFn)fp;
    void* pH;
    cudaGetSymbolAddress(&pH, g_HT);
    bool ok = fn != nullptr;
    {
      const cuuint64_t d[3] = {DM, SEQ / 2, 2}, s[2] = {DM * 2, SEQ * DM};
      const cuuint32_t b[3] = {64, 64, 2};
      ok = ok && encode(fn, &S.m.Xq, d_in[9], 3, d, s, b, CU_TENSOR_MAP_SWIZZLE_128B);
    }
    {
      const cuuint64_t d[5] = {DM, 2, 2, 4, 32}, s[4] = {DM * 2, 8 * DM * 2, 2 * DM * 2, 18 * DM * 2};
      const cuuint32_t b[5] = {64, 2, 2, 4, 32};
      ok = ok && encode(fn, &S.m.Wo, d_in[11], 5, d, s, b, CU_TENSOR_MAP_SWIZZLE_128B);
      const cuuint64_t dt[3] = {DM, 2, 32}, st[2] = {DM * 2, 18 * DM * 2};
      const cuuint32_t bt[3] = {64, 2, 32};
      ok = ok && encode(fn, &S.m.WoT, (const bf16*)d_in[11] + 16 * DM, 3, dt, st, bt, CU_TENSOR_MAP_SWIZZLE_128B);
    }
    ok = ok && encode2(fn, &S.m.H, pH, SEQ, 2 * DM, HT_LD, 64);
    {
      const cuuint64_t d[4] = {64, DM, 32, 2}, s[3] = {HT_LD * 2, 128, (cuuint64_t)DM * HT_LD * 2};
      const cuuint32_t b[4] = {64, 32, 2, 2};
      ok = ok && encode(fn, &S.m.Hs, pH, 4, d, s, b, CU_TENSOR_MAP_SWIZZLE_128B);
    }
    ok = ok && encode2(fn, &S.m.Cre, d_in[5], DM, DM, DM, 128);
    ok = ok && encode2(fn, &S.m.Cim, d_in[6], DM, DM, DM, 128);
    for (cuuint32_t n = 4; n <= 5; n++) {
      const cuuint64_t d[3] = {64, DM, 27}, s[2] = {3456, 128};
      const cuuint32_t b[3] = {64, 64, n};
      ok = ok && encode(fn, n == 4 ? &S.m.W4 : &S.m.W5, d_in[10], 3, d, s, b, CU_TENSOR_MAP_SWIZZLE_128B);
    }
    {
      const char *re = (const char*)d_in[3], *im = (const char*)d_in[4];
      S.swap = im < re;
      const cuuint64_t d[4] = {DM, 8, 2, 72}, s[3] = {DM * 2, (cuuint64_t)(S.swap ? re - im : im - re), 8 * DM * 2};
      const cuuint32_t b[4] = {64, 8, 2, 4};
      ok = ok && encode(fn, &S.m.B, S.swap ? im : re, 4, d, s, b, CU_TENSOR_MAP_SWIZZLE_128B);
    }
    {
      const cuuint64_t d[5] = {DM, 2, 4, 16, 16}, s[4] = {DM * 2, 32 * DM * 2, 2 * DM * 2, 128 * DM * 2};
      const cuuint32_t b[5] = {64, 2, 4, 16, 1};
      ok = ok && encode(fn, &S.m.X, d_in[0], 5, d, s, b, CU_TENSOR_MAP_SWIZZLE_128B);
    }
    set_smem(main_kernel<false>, M_SMEM);
    set_smem(main_kernel<true>, M_SMEM);
    for (int i = 0; i < 12; i++) S.key[i] = d_in[i];
    S.ok = ok;
    if (!ok) return;
  }
  Side sd;
  const int order[8] = {0, 3, 4, 5, 6, 11, 9, 10};
  for (int i = 0; i < 8; i++) sd.pf[i] = (const unsigned char*)d_in[order[i]];
  sd.lre = (const bf16*)d_in[1]; sd.lim = (const bf16*)d_in[2]; sd.ldt = (const bf16*)d_in[7];
  const bf16 *Bx = (const bf16*)d_in[9], *Wq = (const bf16*)d_in[10];
  KvDesc dt;
  for (int i = 0; i < 4; i++) { dt.k[i] = mkdesc(SB + A_BASE + i * A_SLOT, 4096, 128, 0); dt.v[i] = mkdesc(SB + A_BASE + i * A_SLOT + 8192, 128, 4096, 0); }
  (S.swap ? main_kernel<true> : main_kernel<false>)<<<132, 768, M_SMEM, cudaStreamPerThread>>>(S.m, sd, Bx, Wq, dt, (const bf16*)d_in[0],
                                                                                               (const bf16*)d_in[8], (float*)d_out);
}
```
